```python
import torch

def _softmax(x, axis=-1):
    return torch.softmax(x, dim=axis)
def _gelu(x):
    return torch.nn.functional.gelu(x, approximate="tanh")
def _silu(x):
    return torch.nn.functional.silu(x)
def _sigmoid(x):
    return torch.sigmoid(x)
def _layernorm(x, axis=-1, eps=1e-5):
    m = x.mean(dim=axis, keepdim=True)
    v = x.var(dim=axis, keepdim=True, unbiased=False)
    return (x - m) / torch.sqrt(v + eps)
def _scatter_add(tgt, idx, src, axis=0):
    return tgt.clone().index_add_(axis, idx, src)
def _segment_sum(src, seg, n):
    out = torch.zeros((n,) + src.shape[1:], dtype=src.dtype)
    return out.index_add_(0, seg, src)
def _pad(x, pw):
    flat = tuple(v for pair in reversed(pw) for v in pair)
    return torch.nn.functional.pad(x, flat)

kernel_name = 'concat_heads__sliding_block_cached__sliding_block_cached__decode'

def setup_inputs():

    _w = (lambda a: (lambda t: t.to(torch.bfloat16) if t.is_floating_point() else t)(torch.as_tensor(a)))
    def _A_setup():
        B, Sq, D = 4, 1, 576
        Hq, Hkv, Sk, Dh = 32, 16, 8192, 128
        assert Hq % Hkv == 0, (Hq, Hkv)
        return {
            "x": _w((lambda *s: torch.randn(*s, dtype=torch.bfloat16) * 0.8)(B, Sq, D)),
            "k_cache": _w((lambda *s: torch.randn(*s, dtype=torch.bfloat16) * 0.8)(B, Hkv, Sk, Dh)),
            "v_cache": _w((lambda *s: torch.randn(*s, dtype=torch.bfloat16) * 0.05)(B, Hkv, Sk, Dh)),
            "wq": _w((lambda *s: torch.randn(*s, dtype=torch.bfloat16) * 0.8)(D, Hq * Dh) * (D ** -0.5)),
            "wo": _w((lambda *s: torch.randn(*s, dtype=torch.bfloat16) * 0.05)(Hq * Dh, D) * ((Hq * Dh) ** -0.5)),
        }
    _A_in = _A_setup()

    def _B_setup():
        B, Sq, D = 4, 1, 576
        Hq, Hkv, Sk, Dh = 32, 16, 8192, 128
        assert Hq % Hkv == 0, (Hq, Hkv)
        return {
            "x": _w((lambda *s: torch.randn(*s, dtype=torch.bfloat16) * 0.8)(B, Sq, D)),
            "k_cache": _w((lambda *s: torch.randn(*s, dtype=torch.bfloat16) * 0.8)(B, Hkv, Sk, Dh)),
            "v_cache": _w((lambda *s: torch.randn(*s, dtype=torch.bfloat16) * 0.05)(B, Hkv, Sk, Dh)),
            "wq": _w((lambda *s: torch.randn(*s, dtype=torch.bfloat16) * 0.8)(D, Hq * Dh) * (D ** -0.5)),
            "wo": _w((lambda *s: torch.randn(*s, dtype=torch.bfloat16) * 0.05)(Hq * Dh, D) * ((Hq * Dh) ** -0.5)),
        }
    _B_in = _B_setup()

    return {
        "A_x": _A_in["x"],
        "A_k_cache": _A_in["k_cache"],
        "A_v_cache": _A_in["v_cache"],
        "A_wq": _A_in["wq"],
        "A_wo": _A_in["wo"],
        "B_x": _B_in["x"],
        "B_k_cache": _B_in["k_cache"],
        "B_v_cache": _B_in["v_cache"],
        "B_wq": _B_in["wq"],
        "B_wo": _B_in["wo"],
    }

def reference(A_x, A_k_cache, A_v_cache, A_wq, A_wo, B_x, B_k_cache, B_v_cache, B_wq, B_wo):
    def _A_ref(x, k_cache, v_cache, wq, wo):
        B, Sq, D = x.shape
        Hq, Dh = 32, 128
        Hkv, Sk = k_cache.shape[1], k_cache.shape[2]
        W = min(4096, max(256, Sk // 4))
        rep = Hq // Hkv
        q = (lambda x, *d: x.permute(*d))((x @ wq).reshape(B, Sq, Hq, Dh), 0, 2, 1, 3)
        k = (lambda x, n, axis: torch.repeat_interleave(x, n, dim=axis))(k_cache[:, :, Sk - W:, :], rep, axis=1)
        v = (lambda x, n, axis: torch.repeat_interleave(x, n, dim=axis))(v_cache[:, :, Sk - W:, :], rep, axis=1)
        scores = torch.einsum("bhqd,bhkd->bhqk", q, k) * (Dh ** -0.5)
        p = _softmax(scores, axis=-1)
        o = torch.einsum("bhqk,bhkd->bhqd", p, v)
        return (lambda x, *d: x.permute(*d))(o, 0, 2, 1, 3).reshape(B, Sq, Hq * Dh) @ wo

    def _B_ref(x, k_cache, v_cache, wq, wo):
        B, Sq, D = x.shape
        Hq, Dh = 32, 128
        Hkv, Sk = k_cache.shape[1], k_cache.shape[2]
        W = min(4096, max(256, Sk // 4))
        rep = Hq // Hkv
        q = (lambda x, *d: x.permute(*d))((x @ wq).reshape(B, Sq, Hq, Dh), 0, 2, 1, 3)
        k = (lambda x, n, axis: torch.repeat_interleave(x, n, dim=axis))(k_cache[:, :, Sk - W:, :], rep, axis=1)
        v = (lambda x, n, axis: torch.repeat_interleave(x, n, dim=axis))(v_cache[:, :, Sk - W:, :], rep, axis=1)
        scores = torch.einsum("bhqd,bhkd->bhqk", q, k) * (Dh ** -0.5)
        p = _softmax(scores, axis=-1)
        o = torch.einsum("bhqk,bhkd->bhqd", p, v)
        return (lambda x, *d: x.permute(*d))(o, 0, 2, 1, 3).reshape(B, Sq, Hq * Dh) @ wo

    a = _A_ref(A_x, A_k_cache, A_v_cache, A_wq, A_wo)
    b = _B_ref(B_x, B_k_cache, B_v_cache, B_wq, B_wo)
    return torch.concatenate([a, b], axis=-1)
```

```cpp
#include <cuda_runtime.h>
#include <cuda_bf16.h>
#include <cuda.h>
#include <stdint.h>

namespace {

constexpr int NB = 4, DM = 576, HQ = 32, HKV = 16, SK = 8192, DH = 128, WIN = 2048;
constexpr int NCTA = 128;
constexpr int NST = 4;
#define PREWRITE 1
#define POLL_NS 100
#define POLL_BACKOFF do { if (POLL_NS) __nanosleep(POLL_NS); } while (0)
#define REP_FIRST 5
#define REP_LAST 29
#define OPOLL_NS 0
#define NPRE 5
#define WINDOW 4
constexpr int TILE_KEYS = 128;
constexpr int STAGE_BYTES = TILE_KEYS * DH * 2;
constexpr int NTILE = WIN / TILE_KEYS;
constexpr int WBUF_BYTES = 73728;
#define NWO 8
#define SUB 2
constexpr int WO_BOX_BYTES = WBUF_BYTES / NWO;
constexpr int WO_BOX_D = DH / NWO;
constexpr int XPITCH = 1168;

constexpr int OFF_STAGE = 0;
constexpr int OFF_WBUF = OFF_STAGE + NST * STAGE_BYTES;
constexpr int OFF_S = OFF_WBUF + WBUF_BYTES;
constexpr int OFF_Q = OFF_S + 16384;
constexpr int OFF_O = OFF_Q + 512;
constexpr int OFF_ORED = OFF_O + 16 * 36 * 4;
constexpr int OFF_RED = OFF_ORED + 1024;
constexpr int OFF_CTL = OFF_RED + 128;
constexpr int OFF_BAR = OFF_CTL + 16;
constexpr int SMEM_USED = OFF_BAR + 384;
constexpr int SMEM_BYTES = SMEM_USED + 1024;

constexpr int NTHREADS = 288 + 128;
constexpr unsigned SPIN_LIMIT = 1u << 24;

struct Maps { CUtensorMap k[2], v[2], wq[2], wo[2]; };

__device__ __align__(128) unsigned long long g_qx[NCTA * 128];
__device__ __align__(128) unsigned long long g_ox[NCTA * 128];
__device__ __align__(128) unsigned long long g_fx[NCTA * 16 * 36];
__device__ unsigned int g_epoch[NCTA];
__device__ __align__(128) unsigned long long g_prog[2 * 32 * 16];

__device__ __forceinline__ unsigned long long gtime() { unsigned long long t; asm volatile("mov.u64 %0, %%globaltimer;" : "=l"(t)); return t; }
__device__ __forceinline__ uint32_t gtime32() { uint32_t t; asm volatile("mov.u32 %0, %%globaltimer_lo;" : "=r"(t)); return t; }
#define TS(i) do { } while (0)

__device__ __forceinline__ uint32_t smem_u32(const void* p) { return (uint32_t)__cvta_generic_to_shared(p); }
__device__ __forceinline__ void mbar_init(uint32_t a, uint32_t c) { asm volatile("mbarrier.init.shared::cta.b64 [%0], %1;" :: "r"(a), "r"(c) : "memory"); }
__device__ __forceinline__ void mbar_expect_tx(uint32_t a, uint32_t b) { asm volatile("mbarrier.arrive.expect_tx.shared::cta.b64 _, [%0], %1;" :: "r"(a), "r"(b) : "memory"); }
__device__ __forceinline__ void mbar_arrive(uint32_t a) { asm volatile("mbarrier.arrive.shared::cta.b64 _, [%0];" :: "r"(a) : "memory"); }
__device__ __forceinline__ void mbar_wait(uint32_t a, uint32_t ph) {
    uint32_t ok; unsigned it = 0;
    do {
        asm volatile("{\n.reg .pred p;\nmbarrier.try_wait.parity.shared::cta.b64 p, [%1], %2;\nselp.u32 %0, 1, 0, p;\n}"
                     : "=r"(ok) : "r"(a), "r"(ph) : "memory");
        if (++it > SPIN_LIMIT) __trap();
    } while (!ok);
}
__device__ __forceinline__ bool mbar_test(uint32_t a, uint32_t ph) {
    uint32_t ok;
    asm volatile("{\n.reg .pred p;\nmbarrier.test_wait.parity.shared::cta.b64 p, [%1], %2;\nselp.u32 %0, 1, 0, p;\n}"
                 : "=r"(ok) : "r"(a), "r"(ph) : "memory");
    return ok != 0;
}
__device__ __forceinline__ void bulk_g2s(uint32_t dst, const void* src, uint32_t bytes, uint32_t bar) {
    asm volatile("cp.async.bulk.shared::cluster.global.mbarrier::complete_tx::bytes [%0], [%1], %2, [%3];"
                 :: "r"(dst), "l"(src), "r"(bytes), "r"(bar) : "memory");
}
__device__ __forceinline__ void tma2d(uint32_t dst, const CUtensorMap* m, int c0, int c1, uint32_t bar, uint64_t pol) {
    asm volatile("cp.async.bulk.tensor.2d.shared::cluster.global.mbarrier::complete_tx::bytes.L2::cache_hint [%0], [%1, {%3, %4}], [%2], %5;"
                 :: "r"(dst), "l"(m), "r"(bar), "r"(c0), "r"(c1), "l"(pol) : "memory");
}
__device__ __forceinline__ void tma3d(uint32_t dst, const CUtensorMap* m, int c0, int c1, int c2, uint32_t bar) {
    asm volatile("cp.async.bulk.tensor.3d.shared::cluster.global.mbarrier::complete_tx::bytes [%0], [%1, {%3, %4, %5}], [%2];"
                 :: "r"(dst), "l"(m), "r"(bar), "r"(c0), "r"(c1), "r"(c2) : "memory");
}
__device__ __forceinline__ void ldsm4(uint32_t (&r)[4], uint32_t a) {
    asm volatile("ldmatrix.sync.aligned.m8n8.x4.shared.b16 {%0,%1,%2,%3}, [%4];"
                 : "=r"(r[0]), "=r"(r[1]), "=r"(r[2]), "=r"(r[3]) : "r"(a));
}
__device__ __forceinline__ void ldsm4t(uint32_t (&r)[4], uint32_t a) {
    asm volatile("ldmatrix.sync.aligned.m8n8.x4.trans.shared.b16 {%0,%1,%2,%3}, [%4];"
                 : "=r"(r[0]), "=r"(r[1]), "=r"(r[2]), "=r"(r[3]) : "r"(a));
}
__device__ __forceinline__ void mma16816(float (&c)[4], const uint32_t (&a)[4], uint32_t b0, uint32_t b1) {
    asm("mma.sync.aligned.m16n8k16.row.col.f32.bf16.bf16.f32 {%0,%1,%2,%3}, {%4,%5,%6,%7}, {%8,%9}, {%0,%1,%2,%3};"
                 : "+f"(c[0]), "+f"(c[1]), "+f"(c[2]), "+f"(c[3])
                 : "r"(a[0]), "r"(a[1]), "r"(a[2]), "r"(a[3]), "r"(b0), "r"(b1));
}
__device__ __forceinline__ uint32_t lds32(uint32_t a) { uint32_t v; asm volatile("ld.shared.u32 %0, [%1];" : "=r"(v) : "r"(a)); return v; }
__device__ __forceinline__ uint4 lds128(uint32_t a) {
    uint4 v; asm volatile("ld.shared.v4.u32 {%0,%1,%2,%3}, [%4];" : "=r"(v.x), "=r"(v.y), "=r"(v.z), "=r"(v.w) : "r"(a)); return v;
}
__device__ __forceinline__ void bar_sync(int id, int n) { asm volatile("bar.sync %0, %1;" :: "r"(id), "r"(n) : "memory"); }

__device__ __forceinline__ void put_word(unsigned long long* p, uint32_t payload, uint32_t tag) {
    unsigned long long w = ((unsigned long long)tag << 32) | payload;
    asm volatile("st.relaxed.gpu.global.u64 [%0], %1;" :: "l"(p), "l"(w) : "memory");
}
__device__ __forceinline__ void put_word2(unsigned long long* p, uint32_t p0, uint32_t p1, uint32_t tag) {
    unsigned long long w0 = ((unsigned long long)tag << 32) | p0, w1 = ((unsigned long long)tag << 32) | p1;
    asm volatile("st.relaxed.gpu.global.v2.u64 [%0], {%1, %2};" :: "l"(p), "l"(w0), "l"(w1) : "memory");
}
__device__ __forceinline__ unsigned long long ld_word(const unsigned long long* p) {
    unsigned long long w;
    asm volatile("ld.relaxed.gpu.global.u64 %0, [%1];" : "=l"(w) : "l"(p) : "memory");
    return w;
}
__device__ __forceinline__ void ld_word2(const unsigned long long* p, unsigned long long& w0, unsigned long long& w1) {
    asm volatile("ld.relaxed.gpu.global.v2.u64 {%0, %1}, [%2];" : "=l"(w0), "=l"(w1) : "l"(p) : "memory");
}
__device__ __forceinline__ uint32_t get_word(const unsigned long long* p, uint32_t tag) {
    unsigned it = 0;
    unsigned long long w = ld_word(p);
    while ((uint32_t)(w >> 32) != tag) { if (++it > SPIN_LIMIT) __trap(); w = ld_word(p); }
    return (uint32_t)w;
}
__device__ __forceinline__ void get_word_x2(const unsigned long long* p0, const unsigned long long* p1, uint32_t tag, uint32_t& v0, uint32_t& v1) {
    unsigned it = 0;
    unsigned long long w0 = ld_word(p0), w1 = ld_word(p1);
    while ((uint32_t)(w0 >> 32) != tag || (uint32_t)(w1 >> 32) != tag) {
        if (++it > SPIN_LIMIT) __trap();
        w0 = ld_word(p0); w1 = ld_word(p1);
    }
    v0 = (uint32_t)w0; v1 = (uint32_t)w1;
}
__device__ __forceinline__ int tile_slot(int i) { return i < NST + 2 ? i : ((i - NST - 2) & (NST - 1)); }
__device__ __forceinline__ uint32_t tile_par(int i) { return i < NST + 2 ? 0u : (uint32_t)((1 + ((i - NST - 2) >> 2)) & 1); }
__device__ __forceinline__ void pace(uint32_t t_start, int bytes, int tau, const volatile int* offset) {
    const int due = (int)(((long long)bytes * tau) >> 20);
    while ((int)(gtime32() - t_start) < due + *offset) {}
}
__device__ __forceinline__ float bf16r(float v) { return __bfloat162float(__float2bfloat16_rn(v)); }
__device__ __forceinline__ uint32_t pack_bf16(float lo, float hi) {
    __nv_bfloat162 t = __floats2bfloat162_rn(lo, hi);
    return *reinterpret_cast<uint32_t*>(&t);
}

__global__ void __launch_bounds__(NTHREADS, 1)
fused_decode_kernel(const __grid_constant__ Maps maps, const __nv_bfloat16* __restrict__ xA,
                    const __nv_bfloat16* __restrict__ xB, __nv_bfloat16* __restrict__ out, int tau, int delta, int lead, int taper) {
    extern __shared__ unsigned char smem_raw[];
    const uint32_t sb = (smem_u32(smem_raw) + 1023u) & ~1023u;
    unsigned char* sp = smem_raw + (sb - smem_u32(smem_raw));

    const int tid = threadIdx.x, warp = tid >> 5, lane = tid & 31;
    const int g = lane >> 2, t = lane & 3;
    const int cta = blockIdx.x;
    const int br = cta >> 6, hkv = (cta >> 2) & 15, r = cta & 3;

    const uint32_t bar_full = sb + OFF_BAR, bar_empty = bar_full + 8 * (NST + 2);
    const uint32_t bar_wq = bar_empty + 8 * NST, bar_wqfree = bar_wq + 24, bar_o = bar_wqfree + 8, bar_go = bar_o + 8, bar_q = bar_go + 8, bar_wo = bar_q + 8;
    const int row0 = ((r * HKV + hkv) * SK + (SK - WIN)) * 2;

    uint64_t pol = 0;
    uint32_t t_start = 0;
    volatile int* ctl = reinterpret_cast<volatile int*>(sp + OFF_CTL);
    if (tid == 256) {
        TS(0);
        t_start = gtime32();
        for (int i = 0; i < 3; i++) mbar_init(bar_wq + 8 * i, 1);
        asm volatile("fence.mbarrier_init.release.cluster;" ::: "memory");
        asm volatile("createpolicy.fractional.L2::evict_first.b64 %0, 1.0;" : "=l"(pol));
        const __nv_bfloat16* x = br ? xB : xA;
#pragma unroll
        for (int j = 0; j < 3; j++) {
            mbar_expect_tx(bar_wq + 8 * j, WBUF_BYTES / 3 + (j == 0 ? NB * DM * 2 : 0));
            tma2d(sb + OFF_WBUF + j * 192 * 128, &maps.wq[br], hkv * 256 + r * 64, j * 192, bar_wq + 8 * j, pol);
            if (j == 0) {
#pragma unroll
                for (int b = 0; b < NB; b++) bulk_g2s(sb + OFF_S + b * XPITCH, x + b * DM, DM * 2, bar_wq);
            }
        }
        TS(11);
        for (int i = 0; i < NST + 2; i++) mbar_init(bar_full + 8 * i, 1);
        for (int i = 0; i < NST; i++) mbar_init(bar_empty + 8 * i, 8);
        ctl[0] = -delta; ctl[1] = (int)t_start;
        mbar_init(bar_wqfree, 4);
        mbar_init(bar_o, 4);
        mbar_init(bar_go, 1);
        mbar_init(bar_q, 4);
        for (int i = 0; i < NWO; i++) mbar_init(bar_wo + 8 * i, 1);
        asm volatile("fence.mbarrier_init.release.cluster;" ::: "memory");
    }
    const uint32_t tag = *(volatile unsigned int*)&g_epoch[cta] + 1u;
    {
        const int grp = (br * 4 + r) * 16;
        if (tid < 288) put_word2(&g_fx[((grp + tid / 18) * 16 + hkv) * 36 + (tid % 18) * 2], 0u, 0u, 0u);
        else if (tid < 288 + 64) put_word2(&g_ox[cta * 128 + (tid - 288) * 2], 0u, 0u, 0u);
        else if (tid < 416) put_word2(&g_qx[((cta & ~3) + ((tid - 352) >> 4)) * 128 + r * 32 + ((tid - 352) & 15) * 2], 0u, 0u, 0u);
    }
    __syncthreads();

    if (warp > 8) {
        const int b = warp - 9;
        {
            mbar_wait(bar_wqfree, 0);
            const unsigned long long* qsrc = &g_qx[cta * 128 + b * 32 + lane];
            unsigned long long w = ld_word(qsrc);
            unsigned it = 0;
            while ((uint32_t)(w >> 32) != tag) { if (++it > SPIN_LIMIT) __trap(); POLL_BACKOFF; w = ld_word(qsrc); }
            unsigned short* qs = reinterpret_cast<unsigned short*>(sp + OFF_Q) + b * 64 + (lane >> 3) * 16 + (lane & 7);
            qs[0] = (unsigned short)w;
            qs[8] = (unsigned short)(w >> 16);
            __syncwarp();
            if (lane == 0) mbar_arrive(bar_q);
        }
        if (lead > 0 && b < 2 && lane == 0) {
            unsigned long long* prog = &g_prog[(tag & 1) * 32 * 16];
            if (b == 0) {
                const uint32_t t0 = (uint32_t)ctl[1];
                if (cta < 32) g_prog[((tag & 1) ^ 1) * 32 * 16 + cta * 16] = 0ull;
                for (int i = 0; i <= REP_LAST; i++) {
                    mbar_wait(bar_full + 8 * tile_slot(i), tile_par(i));
                    if (i >= REP_FIRST) {
                        const unsigned long long v = (1ull << 40) | (unsigned long long)min(gtime32() - t0, 1u << 24);
                        asm volatile("red.relaxed.gpu.global.add.u64 [%0], %1;" :: "l"(prog + i * 16), "l"(v) : "memory");
                    }
                }
            } else {
                int n = REP_FIRST;
                for (unsigned it = 0; n <= REP_LAST && it < SPIN_LIMIT && !mbar_test(bar_go, 0); it++) {
                    unsigned long long w = ld_word(prog + n * 16);
                    const unsigned long long w1 = ld_word(prog + (n + 1) * 16);
                    if ((w1 >> 40) == NCTA) { w = w1; n++; }
                    if ((w >> 40) == NCTA) {
                        const int avg = (int)((w & ((1ull << 40) - 1)) / NCTA);
                        const int off = avg - (int)(((long long)(WBUF_BYTES + (n + 1) * STAGE_BYTES) * tau) >> 20) - lead;
                        ctl[0] = max(-delta - 4000, min(off, 8000));
                        n++;
                    } else {
                        __nanosleep(200);
                    }
                }
            }
        }
        __syncwarp();
        mbar_wait(bar_go, 0);
        mbar_wait(bar_full + 8 * tile_slot(2 * NTILE - 1), tile_par(2 * NTILE - 1));
        const unsigned long long* src = &g_ox[((cta & ~3) + b) * 128 + lane * 2];
        unsigned long long w[4];
        unsigned it = 0;
        for (;;) {
            ld_word2(src, w[0], w[1]);
            ld_word2(src + 64, w[2], w[3]);
            if ((uint32_t)(w[0] >> 32) == tag && (uint32_t)(w[1] >> 32) == tag && (uint32_t)(w[2] >> 32) == tag && (uint32_t)(w[3] >> 32) == tag) break;
            if (++it > SPIN_LIMIT) __trap();
            if (OPOLL_NS) __nanosleep(OPOLL_NS);
        }
        uint32_t* os = reinterpret_cast<uint32_t*>(sp + OFF_O) + (b * 4 + (lane & 1) * 2) * 36 + (lane >> 1);
        os[0] = (uint32_t)w[0]; os[36] = (uint32_t)w[1];
        os[16] = (uint32_t)w[2]; os[36 + 16] = (uint32_t)w[3];
        __syncwarp();
        if (lane == 0) mbar_arrive(bar_o);
        if (tid == 288) TS(7);
        return;
    }
    if (warp == 8) {
        if (lane == 0) {
            for (int i = 0; i < 2 * NTILE; i++) {
                const int slot = tile_slot(i);
                if (WINDOW < 4 && i >= WINDOW) mbar_wait(bar_full + 8 * tile_slot(i - WINDOW), tile_par(i - WINDOW));
                if (i >= NST + 2) mbar_wait(bar_empty + 8 * slot, tile_par(i) ^ 1);
                else if (i == NST) mbar_wait(bar_wqfree, 0);
                const CUtensorMap* m = (i < NTILE) ? &maps.k[br] : &maps.v[br];
#pragma unroll
                for (int sub = 0; sub < SUB; sub++) {
                    pace(t_start, WBUF_BYTES + i * STAGE_BYTES + sub * (STAGE_BYTES / SUB), tau, ctl);
                    if (sub == 0) mbar_expect_tx(bar_full + 8 * slot, STAGE_BYTES);
                    tma2d(sb + OFF_STAGE + slot * STAGE_BYTES + sub * (STAGE_BYTES / SUB), m, 0,
                          row0 + (i & (NTILE - 1)) * TILE_KEYS * 2 + sub * (TILE_KEYS * 2 / SUB), bar_full + 8 * slot, pol);
                }
            }
            mbar_arrive(bar_go);
#pragma unroll 1
            for (int j = 0; j < NWO; j++) {
                pace(t_start + taper, WBUF_BYTES + 2 * NTILE * STAGE_BYTES + j * WO_BOX_BYTES, tau, ctl);
                mbar_expect_tx(bar_wo + 8 * j, WO_BOX_BYTES);
                tma3d(sb + OFF_WBUF + j * WO_BOX_BYTES, &maps.wo[br], r * 144, j * WO_BOX_D, hkv * 2, bar_wo + 8 * j);
            }
            g_epoch[cta] = tag;
            TS(1);
        }
        __syncwarp();
    } else {
        if (warp < 4) {
            mbar_wait(bar_wq, 0); mbar_wait(bar_wq + 8, 0); mbar_wait(bar_wq + 16, 0);
            if (tid == 0) TS(2);
            float c0[4] = {0.f, 0.f, 0.f, 0.f}, c1[4] = {0.f, 0.f, 0.f, 0.f};
            const int mi = lane >> 3, i8 = lane & 7;
            const uint32_t abase = sb + OFF_WBUF + (i8 + 8 * (mi >> 1)) * 128 + (((2 * warp + (mi & 1)) ^ i8) << 4);
            const uint32_t xb = sb + OFF_S + (g & 3) * XPITCH + t * 4;
#pragma unroll 6
            for (int ks = 0; ks < 36; ks += 2) {
                uint32_t a[4], a2[4];
                ldsm4t(a, abase + ks * 2048);
                ldsm4t(a2, abase + ks * 2048 + 2048);
                uint32_t b0 = lds32(xb + ks * 32), b1 = lds32(xb + ks * 32 + 16);
                uint32_t b2 = lds32(xb + ks * 32 + 32), b3 = lds32(xb + ks * 32 + 48);
                mma16816(c0, a, b0, b1);
                mma16816(c1, a2, b2, b3);
            }
            __syncwarp();
            if (lane == 0) mbar_arrive(bar_wqfree);
            if (t < 2) {
#pragma unroll
                for (int e = 0; e < 2; e++)
                    put_word(&g_qx[((cta & ~3) + 2 * t + e) * 128 + r * 32 + warp * 8 + g],
                             pack_bf16(c0[e] + c1[e], c0[2 + e] + c1[2 + e]), tag);
            }
            if (tid == 0) TS(10);
        }
        mbar_wait(bar_q, 0);
        if (tid == 0) TS(3);

        {
            uint32_t qb[2][4][2];
            const int h = g & 1, sel = (g >> 1) & 1;
#pragma unroll
            for (int p = 0; p < 2; p++)
#pragma unroll
                for (int s = 0; s < 4; s++) {
                    const uint32_t a = sb + OFF_Q + (h * 128 + ((sel ^ p) * 64) + s * 16 + 2 * t) * 2;
                    qb[p][s][0] = lds32(a);
                    qb[p][s][1] = lds32(a + 16);
                }
            const int mi = lane >> 3, i8 = lane & 7;
            const int key = warp * 16 + i8 + 8 * (mi & 1);
            uint32_t koff[2];
#pragma unroll
            for (int p = 0; p < 2; p++) {
                const int j = 2 * key + ((i8 >> 2) ^ p);
                koff[p] = j * 128 + (((mi >> 1) ^ (j & 7)) << 4);
            }
            float2* S = reinterpret_cast<float2*>(sp + OFF_S);
            const bool valid = (t == (g >> 2));
            const float scale = 0.08838834764831845f;
#pragma unroll 1
            for (int it = 0; it < NTILE; it++) {
                const int st = tile_slot(it);
                mbar_wait(bar_full + 8 * st, tile_par(it));
                const uint32_t base = sb + OFF_STAGE + st * STAGE_BYTES;
                float ca[4] = {0.f, 0.f, 0.f, 0.f}, cb[4] = {0.f, 0.f, 0.f, 0.f};
#pragma unroll
                for (int s = 0; s < 4; s++) {
                    uint32_t a[4], a2[4];
                    ldsm4(a, base + (koff[0] ^ (s << 5)));
                    ldsm4(a2, base + (koff[1] ^ (s << 5)));
                    mma16816(ca, a, qb[0][s][0], qb[0][s][1]);
                    mma16816(cb, a2, qb[1][s][0], qb[1][s][1]);
                }
                __syncwarp();
                if (lane == 0 && st < NST) mbar_arrive(bar_empty + 8 * st);
                const float2 s0 = make_float2(bf16r(bf16r(ca[0] + cb[0]) * scale), bf16r(bf16r(ca[1] + cb[1]) * scale));
                const float2 s1 = make_float2(bf16r(bf16r(ca[2] + cb[2]) * scale), bf16r(bf16r(ca[3] + cb[3]) * scale));
                if (valid) {
                    const int k0 = it * TILE_KEYS + warp * 16 + g;
                    S[k0] = s0;
                    S[k0 + 8] = s1;
                }
            }
            bar_sync(1, 256);
        }
        if (tid == 0) TS(4);

        {
            const int gp = tid >> 2, tt = tid & 3;
            float4 sv[4];
#pragma unroll
            for (int j = 0; j < 4; j++)
                sv[j] = *reinterpret_cast<const float4*>(sp + OFF_S + (gp * 32 + j * 8 + 2 * tt) * 8);
            float m0 = -INFINITY, m1 = -INFINITY;
#pragma unroll
            for (int j = 0; j < 4; j++) {
                m0 = fmaxf(m0, fmaxf(sv[j].x, sv[j].z));
                m1 = fmaxf(m1, fmaxf(sv[j].y, sv[j].w));
            }
#pragma unroll
            for (int o = 16; o; o >>= 1) {
                m0 = fmaxf(m0, __shfl_xor_sync(0xffffffffu, m0, o));
                m1 = fmaxf(m1, __shfl_xor_sync(0xffffffffu, m1, o));
            }
            float2* red = reinterpret_cast<float2*>(sp + OFF_RED);
            if (lane == 0) red[warp] = make_float2(m0, m1);
            bar_sync(1, 256);
#pragma unroll
            for (int w = 0; w < 8; w++) { float2 v = red[w]; m0 = fmaxf(m0, v.x); m1 = fmaxf(m1, v.y); }
            float s0 = 0.f, s1 = 0.f;
#pragma unroll
            for (int j = 0; j < 4; j++) {
                sv[j].x = __expf(sv[j].x - m0); sv[j].z = __expf(sv[j].z - m0);
                sv[j].y = __expf(sv[j].y - m1); sv[j].w = __expf(sv[j].w - m1);
                s0 += sv[j].x + sv[j].z; s1 += sv[j].y + sv[j].w;
            }
#pragma unroll
            for (int o = 16; o; o >>= 1) {
                s0 += __shfl_xor_sync(0xffffffffu, s0, o);
                s1 += __shfl_xor_sync(0xffffffffu, s1, o);
            }
            if (lane == 0) red[8 + warp] = make_float2(s0, s1);
            bar_sync(1, 256);
            s0 = 0.f; s1 = 0.f;
#pragma unroll
            for (int w = 0; w < 8; w++) { float2 v = red[8 + w]; s0 += v.x; s1 += v.y; }
            const float i0 = 1.0f / s0, i1 = 1.0f / s1;
            uint4 p0, p1;
            p0.x = pack_bf16(sv[0].x * i0, sv[0].z * i0); p1.x = pack_bf16(sv[0].y * i1, sv[0].w * i1);
            p0.y = pack_bf16(sv[1].x * i0, sv[1].z * i0); p1.y = pack_bf16(sv[1].y * i1, sv[1].w * i1);
            p0.z = pack_bf16(sv[2].x * i0, sv[2].z * i0); p1.z = pack_bf16(sv[2].y * i1, sv[2].w * i1);
            p0.w = pack_bf16(sv[3].x * i0, sv[3].z * i0); p1.w = pack_bf16(sv[3].y * i1, sv[3].w * i1);
            *reinterpret_cast<uint4*>(sp + OFF_S + gp * 128 + tt * 16) = p0;
            *reinterpret_cast<uint4*>(sp + OFF_S + gp * 128 + 64 + tt * 16) = p1;
            bar_sync(1, 256);
        }
        if (tid == 0) TS(5);

        {
            float oa[4] = {0.f, 0.f, 0.f, 0.f}, ob[4] = {0.f, 0.f, 0.f, 0.f};
            const int mt = warp & 3, p = warp >> 2;
            const int mi = lane >> 3, i8 = lane & 7;
            const int j = 2 * (i8 + 8 * (mi >> 1)) + ((i8 >> 2) ^ p);
            const uint32_t voff = j * 128 + (((2 * mt + (mi & 1)) ^ (j & 7)) << 4);
            const bool live = (g < 4) && (((g >> 1) & 1) == ((t >> 1) ^ p));
            const unsigned char* pp = sp + OFF_S + (g & 1) * 64 + t * 16;
#pragma unroll 1
            for (int it = 0; it < NTILE; it++) {
                uint4 pf[4];
#pragma unroll
                for (int q = 0; q < 4; q++) {
                    pf[q] = *reinterpret_cast<const uint4*>(pp + (it * 4 + q) * 128);
                    if (!live) pf[q] = make_uint4(0u, 0u, 0u, 0u);
                }
                const int st = tile_slot(NTILE + it);
                mbar_wait(bar_full + 8 * st, tile_par(NTILE + it));
                const uint32_t base = sb + OFF_STAGE + st * STAGE_BYTES + voff;
#pragma unroll
                for (int q = 0; q < 4; q++) {
                    uint32_t a[4], a2[4];
                    ldsm4t(a, base + q * 8192);
                    ldsm4t(a2, base + q * 8192 + 4096);
                    mma16816(oa, a, pf[q].x, pf[q].y);
                    mma16816(ob, a2, pf[q].z, pf[q].w);
                }
                __syncwarp();
                if (lane == 0) mbar_arrive(bar_empty + 8 * st);
            }
            if (tid == 0) TS(6);
            float4* ored = reinterpret_cast<float4*>(sp + OFF_ORED);
            if (warp >= 4 && t < 2) ored[mt * 16 + g * 2 + t] = make_float4(oa[0] + ob[0], oa[1] + ob[1], oa[2] + ob[2], oa[3] + ob[3]);
            bar_sync(1, 256);
            {
                float4 v = ored[mt * 16 + g * 2 + (t & 1)];
                const int dim = 64 * t + 16 * mt + g;
                const uint32_t w0 = pack_bf16(oa[0] + ob[0] + v.x, oa[1] + ob[1] + v.y);
                const uint32_t w1 = pack_bf16(oa[2] + ob[2] + v.z, oa[3] + ob[3] + v.w);
                if (warp < 4 && t < 2) {
                    put_word(&g_ox[cta * 128 + dim], w0, tag);
                    put_word(&g_ox[cta * 128 + dim + 8], w1, tag);
                }
            }
        }
    }

    {
        float c0[4] = {0.f, 0.f, 0.f, 0.f}, c1[4] = {0.f, 0.f, 0.f, 0.f};
        const int mi = lane >> 3, i8 = lane & 7;
        const uint32_t abase = sb + OFF_WBUF + ((i8 & 1) * WO_BOX_D + (i8 >> 1) + 4 * (mi >> 1)) * 288 + (2 * warp + (mi & 1)) * 16;
        const uint32_t obase = sb + OFF_O + (lane & 15) * 144;
        constexpr int KSB = WO_BOX_D / 8;
        const int grp = (br * 4 + r) * 16;
        unsigned long long* pdst[2];
#pragma unroll
        for (int hf = 0; hf < 2; hf++) {
            const int idx = warp * 64 + hf * 32 + (g * 2 + (t & 1)) * 2;
            const int dest = idx / 36, slot = idx - dest * 36;
            pdst[hf] = &g_fx[((grp + dest) * 16 + hkv) * 36 + slot];
        }
        uint32_t af[NPRE * KSB][4];
#pragma unroll
        for (int j = 0; j < NPRE; j++) {
            mbar_wait(bar_wo + 8 * j, 0);
#pragma unroll
            for (int s = 0; s < KSB; s++) ldsm4t(af[j * KSB + s], abase + j * WO_BOX_BYTES + s * 8 * 288);
        }
        mbar_wait(bar_o, 0);
        uint32_t bf[32];
#pragma unroll
        for (int i = 0; i < 8; i++) {
            uint4 v = make_uint4(0u, 0u, 0u, 0u);
            if (lane < 16) v = lds128(obase + i * 16);
            bf[4 * i] = v.x; bf[4 * i + 1] = v.y; bf[4 * i + 2] = v.z; bf[4 * i + 3] = v.w;
        }
        float c2[4] = {0.f, 0.f, 0.f, 0.f}, c3[4] = {0.f, 0.f, 0.f, 0.f};
#pragma unroll
        for (int ks = 0; ks < NPRE * KSB; ks++) {
            float (&c)[4] = (ks & 3) == 0 ? c0 : (ks & 3) == 1 ? c1 : (ks & 3) == 2 ? c2 : c3;
            mma16816(c, af[ks], bf[2 * ks], bf[2 * ks + 1]);
        }
#pragma unroll
        for (int i = 0; i < 4; i++) { c0[i] += c2[i]; c1[i] += c3[i]; }
#pragma unroll
        for (int j = NPRE; j < NWO; j++) {
            mbar_wait(bar_wo + 8 * j, 0);
            if (tid == 0 && j == NWO - 1) TS(12);
            uint32_t a[KSB][4];
#pragma unroll
            for (int s = 0; s < KSB; s++) ldsm4t(a[s], abase + j * WO_BOX_BYTES + s * 8 * 288);
#pragma unroll
            for (int s = 0; s < KSB; s++) mma16816((s & 1) ? c1 : c0, a[s], bf[2 * (j * KSB + s)], bf[2 * (j * KSB + s) + 1]);
        }
        if (t < 2) {
            put_word2(pdst[0], __float_as_uint(c0[0] + c1[0]), __float_as_uint(c0[1] + c1[1]), tag);
            put_word2(pdst[1], __float_as_uint(c0[2] + c1[2]), __float_as_uint(c0[3] + c1[3]), tag);
        }
        if (tid == 0) TS(8);
        const unsigned long long* fp = &g_fx[(grp + hkv) * 16 * 36 + tid * 2];
        unsigned long long w0 = 0, w1 = 0;
        {
            unsigned it = 0;
            ld_word2(fp, w0, w1);
            while ((uint32_t)(w0 >> 32) != tag || (uint32_t)(w1 >> 32) != tag) { if (++it > SPIN_LIMIT) __trap(); ld_word2(fp, w0, w1); }
        }
        float2* fred = reinterpret_cast<float2*>(sp + OFF_S + 8192);
        fred[tid] = make_float2(__uint_as_float((uint32_t)w0), __uint_as_float((uint32_t)w1));
        bar_sync(2, 288);
        if (tid < 36) {
            const float* fr = reinterpret_cast<const float*>(fred) + tid;
            float acc = 0.f;
#pragma unroll
            for (int i = 0; i < 16; i++) acc += fr[i * 36];
            const int idx = hkv * 36 + tid;
            const int w = idx >> 6, hf = (idx >> 5) & 1, gg = (idx >> 2) & 7, tt = (idx >> 1) & 1, e = idx & 1;
                out[(2 * tt + e) * (2 * DM) + br * DM + r * 144 + w * 16 + gg + 8 * hf] = __float2bfloat16_rn(acc);
        }
        if (tid == 0) TS(9);
    }
}

__device__ float g_fb_q[2 * NB * HQ * DH];
__device__ float g_fb_o[2 * NB * HQ * DH];

struct Ptrs { const __nv_bfloat16 *x[2], *k[2], *v[2], *wq[2], *wo[2]; };

__global__ void fb_qproj(Ptrs p) {
    const int idx = blockIdx.x * blockDim.x + threadIdx.x;
    const int br = idx >> 14, b = (idx >> 12) & 3, col = idx & 4095;
    float acc = 0.f;
    for (int k = 0; k < DM; k++) acc += __bfloat162float(p.x[br][b * DM + k]) * __bfloat162float(p.wq[br][k * 4096 + col]);
    g_fb_q[idx] = bf16r(acc);
}
__global__ void fb_attn(Ptrs p) {
    __shared__ float s[WIN]; __shared__ float q[DH]; __shared__ float red[128];
    const int br = blockIdx.x >> 7, b = (blockIdx.x >> 5) & 3, h = blockIdx.x & 31, tid = threadIdx.x;
    const size_t base = ((size_t)(b * HKV + (h >> 1)) * SK + (SK - WIN)) * DH;
    q[tid] = g_fb_q[blockIdx.x * DH + tid];
    __syncthreads();
    float m = -INFINITY;
    for (int k = tid; k < WIN; k += 128) {
        float acc = 0.f;
        for (int d = 0; d < DH; d++) acc += q[d] * __bfloat162float(p.k[br][base + (size_t)k * DH + d]);
        acc = bf16r(bf16r(acc) * 0.08838834764831845f);
        s[k] = acc; m = fmaxf(m, acc);
    }
    red[tid] = m; __syncthreads();
    for (int i = 0; i < 128; i++) m = fmaxf(m, red[i]);
    __syncthreads();
    float sum = 0.f;
    for (int k = tid; k < WIN; k += 128) { float e = __expf(s[k] - m); s[k] = e; sum += e; }
    red[tid] = sum; __syncthreads();
    sum = 0.f;
    for (int i = 0; i < 128; i++) sum += red[i];
    const float inv = 1.0f / sum;
    float acc = 0.f;
    for (int k = 0; k < WIN; k++) acc += bf16r(s[k] * inv) * __bfloat162float(p.v[br][base + (size_t)k * DH + tid]);
    g_fb_o[blockIdx.x * DH + tid] = bf16r(acc);
}
__global__ void fb_oproj(Ptrs p, __nv_bfloat16* out) {
    const int idx = blockIdx.x * blockDim.x + threadIdx.x;
    if (idx >= NB * 2 * DM) return;
    const int b = idx / (2 * DM), c = idx % (2 * DM), br = c / DM, col = c % DM;
    float acc = 0.f;
    for (int k = 0; k < HQ * DH; k++) acc += g_fb_o[(br * NB + b) * HQ * DH + k] * __bfloat162float(p.wo[br][k * DM + col]);
    out[idx] = __float2bfloat16_rn(acc);
}

typedef CUresult (*EncodeFn)(CUtensorMap*, CUtensorMapDataType, cuuint32_t, void*, const cuuint64_t*, const cuuint64_t*,
                             const cuuint32_t*, const cuuint32_t*, CUtensorMapInterleave, CUtensorMapSwizzle,
                             CUtensorMapL2promotion, CUtensorMapFloatOOBfill);

bool encode_maps(Maps& m, void* const* d_in) {
    void* fn = nullptr;
    cudaDriverEntryPointQueryResult qr;
    if (cudaGetDriverEntryPoint("cuTensorMapEncodeTiled", &fn, cudaEnableDefault, &qr) != cudaSuccess || !fn) return false;
    EncodeFn enc = (EncodeFn)fn;
    const cuuint32_t es[3] = {1, 1, 1};
    bool ok = true;
    for (int br = 0; br < 2; br++) {
        {
            const cuuint64_t dims[2] = {64, (cuuint64_t)NB * HKV * SK * 2}, str[1] = {128};
            const cuuint32_t box[2] = {64, TILE_KEYS * 2 / SUB};
            ok &= enc(&m.k[br], CU_TENSOR_MAP_DATA_TYPE_BFLOAT16, 2, d_in[br * 5 + 1], dims, str, box, es, CU_TENSOR_MAP_INTERLEAVE_NONE,
                      CU_TENSOR_MAP_SWIZZLE_128B, CU_TENSOR_MAP_L2_PROMOTION_L2_256B, CU_TENSOR_MAP_FLOAT_OOB_FILL_NONE) == CUDA_SUCCESS;
            ok &= enc(&m.v[br], CU_TENSOR_MAP_DATA_TYPE_BFLOAT16, 2, d_in[br * 5 + 2], dims, str, box, es, CU_TENSOR_MAP_INTERLEAVE_NONE,
                      CU_TENSOR_MAP_SWIZZLE_128B, CU_TENSOR_MAP_L2_PROMOTION_L2_256B, CU_TENSOR_MAP_FLOAT_OOB_FILL_NONE) == CUDA_SUCCESS;
        }
        {
            const cuuint64_t dims[2] = {(cuuint64_t)HQ * DH, DM}, str[1] = {(cuuint64_t)HQ * DH * 2};
            const cuuint32_t box[2] = {64, 192};
            ok &= enc(&m.wq[br], CU_TENSOR_MAP_DATA_TYPE_BFLOAT16, 2, d_in[br * 5 + 3], dims, str, box, es, CU_TENSOR_MAP_INTERLEAVE_NONE,
                      CU_TENSOR_MAP_SWIZZLE_128B, CU_TENSOR_MAP_L2_PROMOTION_NONE, CU_TENSOR_MAP_FLOAT_OOB_FILL_NONE) == CUDA_SUCCESS;
        }
        {
            const cuuint64_t dims[3] = {DM, DH, HQ}, str[2] = {DM * 2, (cuuint64_t)DM * 2 * DH};
            const cuuint32_t box[3] = {144, WO_BOX_D, 2};
            ok &= enc(&m.wo[br], CU_TENSOR_MAP_DATA_TYPE_BFLOAT16, 3, d_in[br * 5 + 4], dims, str, box, es, CU_TENSOR_MAP_INTERLEAVE_NONE,
                      CU_TENSOR_MAP_SWIZZLE_NONE, CU_TENSOR_MAP_L2_PROMOTION_NONE, CU_TENSOR_MAP_FLOAT_OOB_FILL_NONE) == CUDA_SUCCESS;
        }
    }
    return ok;
}

}

static int g_tau = (int)(1310.0 / 32768.0 * 1048576.0), g_delta = 700, g_lead = 1800, g_taper = 900;

extern "C" void kernel_launch(void* const* d_in, const int* in_sizes, int n_in, void* d_out, int out_size) {
    (void)in_sizes; (void)n_in; (void)out_size;
    static int fast_ok = -1;
    if (fast_ok < 0) {
        int dev = 0, sms = 0, nb = 0;
        bool ok = cudaGetDevice(&dev) == cudaSuccess &&
                  cudaDeviceGetAttribute(&sms, cudaDevAttrMultiProcessorCount, dev) == cudaSuccess &&
                  cudaFuncSetAttribute(fused_decode_kernel, cudaFuncAttributeMaxDynamicSharedMemorySize, SMEM_BYTES) == cudaSuccess &&
                  cudaOccupancyMaxActiveBlocksPerMultiprocessor(&nb, fused_decode_kernel, NTHREADS, SMEM_BYTES) == cudaSuccess &&
                  sms * nb >= NCTA;
        fast_ok = ok ? 1 : 0;
        (void)cudaGetLastError();
    }
    Maps maps;
    if (fast_ok == 1 && encode_maps(maps, d_in)) {
        fused_decode_kernel<<<NCTA, NTHREADS, SMEM_BYTES>>>(maps, (const __nv_bfloat16*)d_in[0], (const __nv_bfloat16*)d_in[5],
                                                           (__nv_bfloat16*)d_out, g_tau, g_delta, g_lead, g_taper);
        return;
    }
    Ptrs p;
    for (int br = 0; br < 2; br++) {
        p.x[br] = (const __nv_bfloat16*)d_in[br * 5 + 0]; p.k[br] = (const __nv_bfloat16*)d_in[br * 5 + 1];
        p.v[br] = (const __nv_bfloat16*)d_in[br * 5 + 2]; p.wq[br] = (const __nv_bfloat16*)d_in[br * 5 + 3];
        p.wo[br] = (const __nv_bfloat16*)d_in[br * 5 + 4];
    }
    fb_qproj<<<2 * NB * HQ * DH / 256, 256>>>(p);
    fb_attn<<<2 * NB * HQ, 128>>>(p);
    fb_oproj<<<(NB * 2 * DM + 127) / 128, 128>>>(p, (__nv_bfloat16*)d_out);
}
```

```cpp
#include <cuda_runtime.h>
#include <cuda_bf16.h>
#include <cuda.h>
#include <stdint.h>

namespace {

constexpr int NB = 4, DM = 576, HQ = 32, HKV = 16, SK = 8192, DH = 128, WIN = 2048;
constexpr int NCTA = 128;
constexpr int NST = 4;
#define POLL_NS 100
#define REP_FIRST 5
#define REP_LAST 29
#define NPRE 5
#define FIXAT 7
#define SUB 2
#define WOPROMO CU_TENSOR_MAP_L2_PROMOTION_L2_128B
constexpr int TILE_KEYS = 128;
constexpr int STAGE_BYTES = TILE_KEYS * DH * 2;
constexpr int NTILE = WIN / TILE_KEYS;
constexpr int WBUF_BYTES = 73728;
constexpr int NOWN = DM / 16;
constexpr int NWO = HKV;
constexpr int WO_BOX_BYTES = 256 * 32;
constexpr int WO_STEP = WBUF_BYTES / NWO;
constexpr int XPITCH = 1168;

constexpr int OFF_STAGE = 0;
constexpr int OFF_WBUF = OFF_STAGE + NST * STAGE_BYTES;
constexpr int OFF_S = OFF_WBUF + WBUF_BYTES;
constexpr int OFF_WO = OFF_S - NWO * WO_BOX_BYTES;
constexpr int OFF_Q = OFF_S + 16384;
constexpr int OFF_ORED = OFF_Q + 512;
constexpr int OFF_RED = OFF_ORED + 2 * 288 * 4;
constexpr int OFF_CTL = OFF_RED + 128;
constexpr int OFF_BAR = OFF_CTL + 16;
constexpr int SMEM_USED = OFF_BAR + 384;
constexpr int SMEM_BYTES = SMEM_USED + 1024;

constexpr int NTHREADS = 352;
constexpr unsigned SPIN_LIMIT = 1u << 24;

struct Maps { CUtensorMap k[2], v[2], wq[2], wo[2]; };

__device__ __align__(128) unsigned long long g_qx[NCTA * 128];
__device__ __align__(128) uint32_t g_ox[NCTA * 128];
__device__ __align__(128) unsigned int g_ready[32];
__device__ unsigned int g_epoch[NCTA];
__device__ __align__(128) unsigned long long g_prog[2 * 32 * 16];

__device__ __forceinline__ uint32_t gtime32() { uint32_t t; asm volatile("mov.u32 %0, %%globaltimer_lo;" : "=r"(t)); return t; }
#define TS(i) do { } while (0)

__device__ __forceinline__ uint32_t smem_u32(const void* p) { return (uint32_t)__cvta_generic_to_shared(p); }
__device__ __forceinline__ void mbar_init(uint32_t a, uint32_t c) { asm volatile("mbarrier.init.shared::cta.b64 [%0], %1;" :: "r"(a), "r"(c) : "memory"); }
__device__ __forceinline__ void mbar_expect_tx(uint32_t a, uint32_t b) { asm volatile("mbarrier.arrive.expect_tx.shared::cta.b64 _, [%0], %1;" :: "r"(a), "r"(b) : "memory"); }
__device__ __forceinline__ void mbar_arrive(uint32_t a) { asm volatile("mbarrier.arrive.shared::cta.b64 _, [%0];" :: "r"(a) : "memory"); }
__device__ __forceinline__ void mbar_wait(uint32_t a, uint32_t ph) {
    uint32_t ok; unsigned it = 0;
    do {
        asm volatile("{\n.reg .pred p;\nmbarrier.try_wait.parity.shared::cta.b64 p, [%1], %2;\nselp.u32 %0, 1, 0, p;\n}"
                     : "=r"(ok) : "r"(a), "r"(ph) : "memory");
        if (++it > SPIN_LIMIT) __trap();
    } while (!ok);
}
__device__ __forceinline__ bool mbar_test(uint32_t a, uint32_t ph) {
    uint32_t ok;
    asm volatile("{\n.reg .pred p;\nmbarrier.test_wait.parity.shared::cta.b64 p, [%1], %2;\nselp.u32 %0, 1, 0, p;\n}"
                 : "=r"(ok) : "r"(a), "r"(ph) : "memory");
    return ok != 0;
}
__device__ __forceinline__ void bulk_g2s(uint32_t dst, const void* src, uint32_t bytes, uint32_t bar) {
    asm volatile("cp.async.bulk.shared::cluster.global.mbarrier::complete_tx::bytes [%0], [%1], %2, [%3];"
                 :: "r"(dst), "l"(src), "r"(bytes), "r"(bar) : "memory");
}
__device__ __forceinline__ void tma2d(uint32_t dst, const CUtensorMap* m, int c0, int c1, uint32_t bar, uint64_t pol) {
    asm volatile("cp.async.bulk.tensor.2d.shared::cluster.global.mbarrier::complete_tx::bytes.L2::cache_hint [%0], [%1, {%3, %4}], [%2], %5;"
                 :: "r"(dst), "l"(m), "r"(bar), "r"(c0), "r"(c1), "l"(pol) : "memory");
}
__device__ __forceinline__ void tma2d_nohint(uint32_t dst, const CUtensorMap* m, int c0, int c1, uint32_t bar) {
    asm volatile("cp.async.bulk.tensor.2d.shared::cluster.global.mbarrier::complete_tx::bytes [%0], [%1, {%3, %4}], [%2];"
                 :: "r"(dst), "l"(m), "r"(bar), "r"(c0), "r"(c1) : "memory");
}
__device__ __forceinline__ void ldsm4(uint32_t (&r)[4], uint32_t a) {
    asm volatile("ldmatrix.sync.aligned.m8n8.x4.shared.b16 {%0,%1,%2,%3}, [%4];"
                 : "=r"(r[0]), "=r"(r[1]), "=r"(r[2]), "=r"(r[3]) : "r"(a));
}
__device__ __forceinline__ void ldsm4t(uint32_t (&r)[4], uint32_t a) {
    asm volatile("ldmatrix.sync.aligned.m8n8.x4.trans.shared.b16 {%0,%1,%2,%3}, [%4];"
                 : "=r"(r[0]), "=r"(r[1]), "=r"(r[2]), "=r"(r[3]) : "r"(a));
}
__device__ __forceinline__ void mma16816(float (&c)[4], const uint32_t (&a)[4], uint32_t b0, uint32_t b1) {
    asm("mma.sync.aligned.m16n8k16.row.col.f32.bf16.bf16.f32 {%0,%1,%2,%3}, {%4,%5,%6,%7}, {%8,%9}, {%0,%1,%2,%3};"
                 : "+f"(c[0]), "+f"(c[1]), "+f"(c[2]), "+f"(c[3])
                 : "r"(a[0]), "r"(a[1]), "r"(a[2]), "r"(a[3]), "r"(b0), "r"(b1));
}
__device__ __forceinline__ uint32_t lds32(uint32_t a) { uint32_t v; asm volatile("ld.shared.u32 %0, [%1];" : "=r"(v) : "r"(a)); return v; }
__device__ __forceinline__ void bar_sync(int id, int n) { asm volatile("bar.sync %0, %1;" :: "r"(id), "r"(n) : "memory"); }

__device__ __forceinline__ void st_word(uint32_t* p, uint32_t w) { asm volatile("st.relaxed.gpu.global.u32 [%0], %1;" :: "l"(p), "r"(w) : "memory"); }
__device__ __forceinline__ void st_u64(unsigned long long* p, unsigned long long w) { asm volatile("st.relaxed.gpu.global.u64 [%0], %1;" :: "l"(p), "l"(w) : "memory"); }
__device__ __forceinline__ void st_zero4(uint32_t* p) { asm volatile("st.relaxed.gpu.global.v4.u32 [%0], {%1, %1, %1, %1};" :: "l"(p), "r"(0u) : "memory"); }
__device__ __forceinline__ uint4 ld_word4(const uint32_t* p) {
    uint4 v;
    asm volatile("ld.relaxed.gpu.global.v4.u32 {%0, %1, %2, %3}, [%4];" : "=r"(v.x), "=r"(v.y), "=r"(v.z), "=r"(v.w) : "l"(p) : "memory");
    return v;
}
__device__ __forceinline__ bool all_set(const uint4& v) { return min(min(v.x, v.y), min(v.z, v.w)) != 0u; }
__device__ __forceinline__ unsigned long long ld_u64(const unsigned long long* p) {
    unsigned long long w;
    asm volatile("ld.relaxed.gpu.global.u64 %0, [%1];" : "=l"(w) : "l"(p) : "memory");
    return w;
}
__device__ __forceinline__ int tile_slot(int i) { return i < NST + 2 ? i : ((i - NST - 2) & (NST - 1)); }
__device__ __forceinline__ uint32_t tile_par(int i) { return i < NST + 2 ? 0u : (uint32_t)((1 + ((i - NST - 2) >> 2)) & 1); }
__device__ __forceinline__ int cum_bytes(int i) { return WBUF_BYTES + i * STAGE_BYTES; }
__device__ __forceinline__ void pace(uint32_t t_start, int bytes, int tau, const volatile int* offset) {
    const int due = (int)(((long long)bytes * tau) >> 20);
    while ((int)(gtime32() - t_start) < due + *offset) {}
}
__device__ __forceinline__ float bf16r(float v) { return __bfloat162float(__float2bfloat16_rn(v)); }
__device__ __forceinline__ uint32_t pack_bf16(float lo, float hi) {
    __nv_bfloat162 t = __floats2bfloat162_rn(lo, hi);
    return *reinterpret_cast<uint32_t*>(&t);
}

__global__ void __launch_bounds__(NTHREADS, 1)
fused_decode_kernel(const __nv_bfloat16* __restrict__ xA, const __nv_bfloat16* __restrict__ xB, __nv_bfloat16* __restrict__ out,
                    int tau, int delta, int lead, int taper, int ow, int ostep,
                    const __grid_constant__ Maps maps) {
    extern __shared__ unsigned char smem_raw[];
    const uint32_t sb = (smem_u32(smem_raw) + 1023u) & ~1023u;
    unsigned char* sp = smem_raw + (sb - smem_u32(smem_raw));

    const int tid = threadIdx.x, warp = tid >> 5, lane = tid & 31;
    const int g = lane >> 2, t = lane & 3;
    const int cta = blockIdx.x;
    const int br = cta >> 6, hkv = (cta >> 2) & 15, r = cta & 3;
    const int strip = !(cta & 1) ? (cta & 63) >> 1 : (cta & 15) == 1 ? 32 + ((cta & 63) >> 4) : NOWN;

    const uint32_t bar_full = sb + OFF_BAR, bar_empty = bar_full + 8 * (NST + 2);
    const uint32_t bar_wq = bar_empty + 8 * NST, bar_wqfree = bar_wq + 24, bar_go = bar_wqfree + 8, bar_q = bar_go + 8, bar_rdy = bar_q + 8, bar_wo = bar_rdy + 8;
    const int row0 = ((r * HKV + hkv) * SK + (SK - WIN)) * 2;

    uint64_t pol = 0;
    uint32_t t_start = 0;
    volatile int* ctl = reinterpret_cast<volatile int*>(sp + OFF_CTL);
    if (warp < 3 && lane == 0) {
        if (tid == 0) TS(0);
        mbar_init(bar_wq + 8 * warp, 1);
        asm volatile("fence.mbarrier_init.release.cluster;" ::: "memory");
        asm volatile("createpolicy.fractional.L2::evict_first.b64 %0, 1.0;" : "=l"(pol));
        mbar_expect_tx(bar_wq + 8 * warp, WBUF_BYTES / 3 + (warp == 0 ? NB * DM * 2 : 0));
        tma2d(sb + OFF_WBUF + warp * 192 * 128, &maps.wq[br], hkv * 256 + r * 64, warp * 192, bar_wq + 8 * warp, pol);
        if (warp == 0) {
            const __nv_bfloat16* x = br ? xB : xA;
#pragma unroll
            for (int b = 0; b < NB; b++) bulk_g2s(sb + OFF_S + b * XPITCH, x + b * DM, DM * 2, bar_wq);
            TS(11);
        }
    }
    if (tid == 256) {
        t_start = gtime32();
        asm volatile("createpolicy.fractional.L2::evict_first.b64 %0, 1.0;" : "=l"(pol));
        for (int i = 0; i < NST + 2; i++) mbar_init(bar_full + 8 * i, 1);
        for (int i = 0; i < NST; i++) mbar_init(bar_empty + 8 * i, 8);
        ctl[0] = -delta; ctl[1] = (int)t_start;
        mbar_init(bar_wqfree, 4);
        mbar_init(bar_go, 1);
        mbar_init(bar_q, 1);
        mbar_init(bar_rdy, 2);
        for (int i = 0; i < NWO; i++) mbar_init(bar_wo + 8 * i, 1);
        asm volatile("fence.mbarrier_init.release.cluster;" ::: "memory");
        for (int i = 0; i < NWO; i++) mbar_expect_tx(bar_wo + 8 * i, WO_BOX_BYTES);
    }
    const uint32_t epoch = *(volatile unsigned int*)&g_epoch[cta] + 1u;
    if (warp == 10) st_zero4(&g_ox[cta * 128 + lane * 4]);
    if (warp == 4 || warp == 5) st_zero4(reinterpret_cast<uint32_t*>(&g_qx[((cta & ~3) + ((tid - 128) >> 4)) * 128 + r * 32 + (lane & 15) * 2]));
    __syncthreads();

    if (warp == 9) {
        mbar_wait(bar_wqfree, 0);
        const uint32_t* qsrc = reinterpret_cast<const uint32_t*>(&g_qx[cta * 128 + lane * 4]);
        uint4 w, w2;
        for (unsigned it = 0;; it++) {
            w = ld_word4(qsrc); w2 = ld_word4(qsrc + 4);
            if (w.y == epoch && w.w == epoch && w2.y == epoch && w2.w == epoch) break;
            if (it > SPIN_LIMIT) __trap();
            __nanosleep(POLL_NS);
        }
        w.y = w.z; w.z = w2.x; w.w = w2.z;
        uint2* qs = reinterpret_cast<uint2*>(sp + OFF_Q + (lane >> 1) * 32 + (lane & 1) * 8);
        qs[0] = make_uint2(__byte_perm(w.x, w.y, 0x5410), __byte_perm(w.z, w.w, 0x5410));
        qs[2] = make_uint2(__byte_perm(w.x, w.y, 0x7632), __byte_perm(w.z, w.w, 0x7632));
        __syncwarp();
        if (lane == 0) {
            mbar_arrive(bar_q);
            unsigned long long* prog = &g_prog[(epoch & 1) * 32 * 16];
            const uint32_t t0 = (uint32_t)ctl[1];
            for (int i = 0; i <= REP_LAST; i++) {
                mbar_wait(bar_full + 8 * tile_slot(i), tile_par(i));
                if (i >= REP_FIRST) {
                    const unsigned long long v = (1ull << 40) | (unsigned long long)min(gtime32() - t0, 1u << 24);
                    asm volatile("red.relaxed.gpu.global.add.u64 [%0], %1;" :: "l"(prog + i * 16), "l"(v) : "memory");
                }
            }
        }
        return;
    }
    if (warp == 10) {
        if (lane == 0) {
            asm volatile("red.release.gpu.global.add.u32 [%0], %1;" :: "l"(g_ready), "r"(1u) : "memory");
            g_epoch[cta] = epoch;
            if (cta < 32) g_prog[((epoch & 1) ^ 1) * 32 * 16 + cta * 16] = 0ull;
            const unsigned long long* prog = &g_prog[(epoch & 1) * 32 * 16];
            mbar_wait(bar_full + 8 * tile_slot(REP_FIRST - 1), tile_par(REP_FIRST - 1));
            for (unsigned it = 0;; it++) {
                unsigned v;
                asm volatile("ld.acquire.gpu.global.u32 %0, [%1];" : "=r"(v) : "l"(g_ready) : "memory");
                if ((int)(v - epoch * NCTA) >= 0) break;
                if (it > SPIN_LIMIT) __trap();
                __nanosleep(200);
            }
            mbar_arrive(bar_rdy);
            TS(13);
            int n = REP_FIRST;
            for (unsigned it = 0; n <= REP_LAST && it < SPIN_LIMIT && !mbar_test(bar_go, 0); it++) {
                unsigned long long w = ld_u64(prog + n * 16);
                const unsigned long long w1 = ld_u64(prog + (n + 1) * 16);
                if ((w1 >> 40) == NCTA) { w = w1; n++; }
                if ((w >> 40) == NCTA) {
                    const int avg = (int)((w & ((1ull << 40) - 1)) / NCTA);
                    const int off = avg - (int)(((long long)cum_bytes(n + 1) * tau) >> 20) - lead;
                    ctl[0] = max(-delta - 4000, min(off, 8000));
                    n++;
                } else {
                    __nanosleep(200);
                }
            }
        }
        return;
    }
    if (warp == 8) {
        if (lane == 0) {
            for (int i = 0; i < 2 * NTILE; i++) {
                const int slot = tile_slot(i);
                if (i >= NST + 2) mbar_wait(bar_empty + 8 * slot, tile_par(i) ^ 1);
                else if (i == NST) mbar_wait(bar_wqfree, 0);
                const CUtensorMap* m = (i < NTILE) ? &maps.k[br] : &maps.v[br];
#pragma unroll
                for (int sub = 0; sub < SUB; sub++) {
                    pace(t_start, cum_bytes(i) + sub * (STAGE_BYTES / SUB), tau, ctl);
                    if (sub == 0) mbar_expect_tx(bar_full + 8 * slot, STAGE_BYTES);
                    tma2d(sb + OFF_STAGE + slot * STAGE_BYTES + sub * (STAGE_BYTES / SUB), m, 0,
                          row0 + (i & (NTILE - 1)) * TILE_KEYS * 2 + sub * (TILE_KEYS * 2 / SUB), bar_full + 8 * slot, pol);
                }
            }
            mbar_arrive(bar_go);
            if (strip < NOWN) {
                mbar_wait(bar_empty + 8 * tile_slot(2 * NTILE), tile_par(2 * NTILE) ^ 1);
                mbar_wait(bar_empty + 8 * tile_slot(2 * NTILE + 1), tile_par(2 * NTILE + 1) ^ 1);
                uint32_t due = t_start + taper + ctl[0] + (int)(((long long)cum_bytes(2 * NTILE) * tau) >> 20);
                const uint32_t step = (uint32_t)(((long long)ostep * tau) >> 20);
                const CUtensorMap* m = &maps.wo[br];
#pragma unroll 1
                for (int i = 0; i < NWO; i++, due += step) {
                    while ((int)(gtime32() - due) < 0) {}
                    tma2d_nohint(sb + OFF_WO + i * WO_BOX_BYTES, m, strip * 16, i * 256, bar_wo + 8 * i);
                    if (i == ow) mbar_arrive(bar_rdy);
                }
            }
            TS(1);
        }
        return;
    }
    {
        if (warp < 4) {
            mbar_wait(bar_wq, 0); mbar_wait(bar_wq + 8, 0); mbar_wait(bar_wq + 16, 0);
            if (tid == 0) TS(2);
            float c0[4] = {0.f, 0.f, 0.f, 0.f}, c1[4] = {0.f, 0.f, 0.f, 0.f};
            const int mi = lane >> 3, i8 = lane & 7;
            const uint32_t abase = sb + OFF_WBUF + (i8 + 8 * (mi >> 1)) * 128 + (((2 * warp + (mi & 1)) ^ i8) << 4);
            const uint32_t xb = sb + OFF_S + (g & 3) * XPITCH + t * 4;
#pragma unroll 6
            for (int ks = 0; ks < 36; ks += 2) {
                uint32_t a[4], a2[4];
                ldsm4t(a, abase + ks * 2048);
                ldsm4t(a2, abase + ks * 2048 + 2048);
                uint32_t b0 = lds32(xb + ks * 32), b1 = lds32(xb + ks * 32 + 16);
                uint32_t b2 = lds32(xb + ks * 32 + 32), b3 = lds32(xb + ks * 32 + 48);
                mma16816(c0, a, b0, b1);
                mma16816(c1, a2, b2, b3);
            }
            __syncwarp();
            if (lane == 0) mbar_arrive(bar_wqfree);
            if (t < 2) {
#pragma unroll
                for (int e = 0; e < 2; e++)
                    st_u64(&g_qx[((cta & ~3) + 2 * t + e) * 128 + r * 32 + warp * 8 + g],
                           ((unsigned long long)epoch << 32) | pack_bf16(c0[e] + c1[e], c0[2 + e] + c1[2 + e]));
            }
            if (tid == 0) TS(10);
        }
        mbar_wait(bar_q, 0);
        if (tid == 0) TS(3);

        {
            uint32_t qb[2][4][2];
            const int h = g & 1, sel = (g >> 1) & 1;
#pragma unroll
            for (int p = 0; p < 2; p++)
#pragma unroll
                for (int s = 0; s < 4; s++) {
                    const uint32_t a = sb + OFF_Q + (h * 128 + ((sel ^ p) * 64) + s * 16 + 2 * t) * 2;
                    qb[p][s][0] = lds32(a);
                    qb[p][s][1] = lds32(a + 16);
                }
            const int mi = lane >> 3, i8 = lane & 7;
            const int key = warp * 16 + i8 + 8 * (mi & 1);
            uint32_t koff[2];
#pragma unroll
            for (int p = 0; p < 2; p++) {
                const int j = 2 * key + ((i8 >> 2) ^ p);
                koff[p] = j * 128 + (((mi >> 1) ^ (j & 7)) << 4);
            }
            float2* S = reinterpret_cast<float2*>(sp + OFF_S);
            const bool valid = (t == (g >> 2));
            const float scale = 0.08838834764831845f;
#pragma unroll 1
            for (int it = 0; it < NTILE; it++) {
                const int st = tile_slot(it);
                mbar_wait(bar_full + 8 * st, tile_par(it));
                const uint32_t base = sb + OFF_STAGE + st * STAGE_BYTES;
                float ca[4] = {0.f, 0.f, 0.f, 0.f}, cb[4] = {0.f, 0.f, 0.f, 0.f};
#pragma unroll
                for (int s = 0; s < 4; s++) {
                    uint32_t a[4], a2[4];
                    ldsm4(a, base + (koff[0] ^ (s << 5)));
                    ldsm4(a2, base + (koff[1] ^ (s << 5)));
                    mma16816(ca, a, qb[0][s][0], qb[0][s][1]);
                    mma16816(cb, a2, qb[1][s][0], qb[1][s][1]);
                }
                __syncwarp();
                if (lane == 0 && st < NST) mbar_arrive(bar_empty + 8 * st);
                const float2 s0 = make_float2(bf16r(bf16r(ca[0] + cb[0]) * scale), bf16r(bf16r(ca[1] + cb[1]) * scale));
                const float2 s1 = make_float2(bf16r(bf16r(ca[2] + cb[2]) * scale), bf16r(bf16r(ca[3] + cb[3]) * scale));
                if (valid) {
                    const int k0 = it * TILE_KEYS + warp * 16 + g;
                    S[k0] = s0;
                    S[k0 + 8] = s1;
                }
            }
            bar_sync(1, 256);
        }
        if (tid == 0) TS(4);

        {
            const int gp = tid >> 2, tt = tid & 3;
            float4 sv[4];
#pragma unroll
            for (int j = 0; j < 4; j++)
                sv[j] = *reinterpret_cast<const float4*>(sp + OFF_S + (gp * 32 + j * 8 + 2 * tt) * 8);
            float m0 = -INFINITY, m1 = -INFINITY;
#pragma unroll
            for (int j = 0; j < 4; j++) {
                m0 = fmaxf(m0, fmaxf(sv[j].x, sv[j].z));
                m1 = fmaxf(m1, fmaxf(sv[j].y, sv[j].w));
            }
#pragma unroll
            for (int o = 16; o; o >>= 1) {
                m0 = fmaxf(m0, __shfl_xor_sync(0xffffffffu, m0, o));
                m1 = fmaxf(m1, __shfl_xor_sync(0xffffffffu, m1, o));
            }
            float2* red = reinterpret_cast<float2*>(sp + OFF_RED);
            if (lane == 0) red[warp] = make_float2(m0, m1);
            bar_sync(1, 256);
#pragma unroll
            for (int w = 0; w < 8; w++) { float2 v = red[w]; m0 = fmaxf(m0, v.x); m1 = fmaxf(m1, v.y); }
            float s0 = 0.f, s1 = 0.f;
#pragma unroll
            for (int j = 0; j < 4; j++) {
                sv[j].x = __expf(sv[j].x - m0); sv[j].z = __expf(sv[j].z - m0);
                sv[j].y = __expf(sv[j].y - m1); sv[j].w = __expf(sv[j].w - m1);
                s0 += sv[j].x + sv[j].z; s1 += sv[j].y + sv[j].w;
            }
#pragma unroll
            for (int o = 16; o; o >>= 1) {
                s0 += __shfl_xor_sync(0xffffffffu, s0, o);
                s1 += __shfl_xor_sync(0xffffffffu, s1, o);
            }
            if (lane == 0) red[8 + warp] = make_float2(s0, s1);
            bar_sync(1, 256);
            s0 = 0.f; s1 = 0.f;
#pragma unroll
            for (int w = 0; w < 8; w++) { float2 v = red[8 + w]; s0 += v.x; s1 += v.y; }
            const float i0 = 1.0f / s0, i1 = 1.0f / s1;
            uint4 p0, p1;
            p0.x = pack_bf16(sv[0].x * i0, sv[0].z * i0); p1.x = pack_bf16(sv[0].y * i1, sv[0].w * i1);
            p0.y = pack_bf16(sv[1].x * i0, sv[1].z * i0); p1.y = pack_bf16(sv[1].y * i1, sv[1].w * i1);
            p0.z = pack_bf16(sv[2].x * i0, sv[2].z * i0); p1.z = pack_bf16(sv[2].y * i1, sv[2].w * i1);
            p0.w = pack_bf16(sv[3].x * i0, sv[3].z * i0); p1.w = pack_bf16(sv[3].y * i1, sv[3].w * i1);
            *reinterpret_cast<uint4*>(sp + OFF_S + gp * 128 + tt * 16) = p0;
            *reinterpret_cast<uint4*>(sp + OFF_S + gp * 128 + 64 + tt * 16) = p1;
            bar_sync(1, 256);
        }
        if (tid == 0) TS(5);

        {
            float oa[4] = {0.f, 0.f, 0.f, 0.f}, ob[4] = {0.f, 0.f, 0.f, 0.f};
            const int mt = warp & 3, p = warp >> 2;
            const int mi = lane >> 3, i8 = lane & 7;
            const int j = 2 * (i8 + 8 * (mi >> 1)) + ((i8 >> 2) ^ p);
            const uint32_t voff = j * 128 + (((2 * mt + (mi & 1)) ^ (j & 7)) << 4);
            const bool live = (g < 4) && (((g >> 1) & 1) == ((t >> 1) ^ p));
            const unsigned char* pp = sp + OFF_S + (g & 1) * 64 + t * 16;
#pragma unroll 1
            for (int it = 0; it < NTILE; it++) {
                uint4 pf[4];
#pragma unroll
                for (int q = 0; q < 4; q++) {
                    pf[q] = *reinterpret_cast<const uint4*>(pp + (it * 4 + q) * 128);
                    if (!live) pf[q] = make_uint4(0u, 0u, 0u, 0u);
                }
                const int st = tile_slot(NTILE + it);
                mbar_wait(bar_full + 8 * st, tile_par(NTILE + it));
                const uint32_t base = sb + OFF_STAGE + st * STAGE_BYTES + voff;
#pragma unroll
                for (int q = 0; q < 4; q++) {
                    uint32_t a[4], a2[4];
                    ldsm4t(a, base + q * 8192);
                    ldsm4t(a2, base + q * 8192 + 4096);
                    mma16816(oa, a, pf[q].x, pf[q].y);
                    mma16816(ob, a2, pf[q].z, pf[q].w);
                }
                __syncwarp();
                if (lane == 0) mbar_arrive(bar_empty + 8 * st);
            }
            if (tid == 0) TS(6);
            float* ored = reinterpret_cast<float*>(sp + OFF_ORED);
            if (t < 2) {
                float* d = ored + p * 288 + 72 * t + 16 * mt + g;
                d[0] = oa[0] + ob[0]; d[144] = oa[1] + ob[1]; d[8] = oa[2] + ob[2]; d[152] = oa[3] + ob[3];
            }
            bar_sync(1, 256);
            if (warp < 4) {
                const float* s = ored + 72 * warp + 32 * (lane >> 4) + 8 * (lane & 3) + 2 * ((lane >> 2) & 3);
                const float2 u = *reinterpret_cast<const float2*>(s), v = *reinterpret_cast<const float2*>(s + 288);
                const uint32_t w = pack_bf16(u.x + v.x, u.y + v.y);
                st_word(&g_ox[cta * 128 + tid], w ? w : 0x8000u);
            }
        }
    }
    if (strip >= NOWN) return;

    {
        const int mi = lane >> 3, i8 = lane & 7, kg = warp & 3, bp = warp >> 2;
        const uint32_t abase = sb + OFF_WO + (64 * kg + i8 + 8 * (mi >> 1)) * 32 + (((mi & 1) ^ (i8 >> 2)) << 4);
        const uint32_t* osrc = &g_ox[(br * 64 + bp * 4 + (g & 3)) * 128 + kg * 32 + (g >> 2) * 16 + t * 4];
        uint32_t abox = abase + bp * WO_BOX_BYTES, bbox = bar_wo + 8 * bp;
        __nv_bfloat16* dst = out + ((tid >> 4) & 3) * (2 * DM) + br * DM + strip * 16 + (tid & 15);
        asm volatile("" : "+l"(osrc), "+r"(abox), "+r"(bbox), "+l"(dst));
        float c[4][4];
#pragma unroll
        for (int i = 0; i < 16; i++) (&c[0][0])[i] = 0.f;
        auto box_mma = [&](int q, const uint4& b) {
            uint32_t a[4][4];
#pragma unroll
            for (int s = 0; s < 4; s++) ldsm4t(a[s], abox + q * 2 * WO_BOX_BYTES + s * 512);
            mma16816(c[0], a[0], b.x, b.y);
            mma16816(c[1], a[1], b.z, b.w);
            mma16816(c[2], a[2], b.x, b.y);
            mma16816(c[3], a[3], b.z, b.w);
        };
        uint4 of[8], nx[8];
        mbar_wait(bar_rdy, 0);
        if (tid == 0) TS(8);
#pragma unroll
        for (int q = 0; q < 8; q++) of[q] = ld_word4(osrc + q * 8 * 128);
        uint32_t af[NPRE][4][4];
#pragma unroll
        for (int q = 0; q < NPRE; q++) {
            mbar_wait(bbox + 16 * q, 0);
#pragma unroll
            for (int s = 0; s < 4; s++) ldsm4t(af[q][s], abox + q * 2 * WO_BOX_BYTES + s * 512);
        }
        uint32_t miss = 0;
#pragma unroll
        for (int q = 0; q < NPRE; q++) {
            mma16816(c[0], af[q][0], of[q].x, of[q].y);
            mma16816(c[1], af[q][1], of[q].z, of[q].w);
            mma16816(c[2], af[q][2], of[q].x, of[q].y);
            mma16816(c[3], af[q][3], of[q].z, of[q].w);
        }
#pragma unroll
        for (int q = 0; q < 8; q++) {
            const bool m = !all_set(of[q]);
            if (m) nx[q] = ld_word4(osrc + q * 8 * 128);
            miss |= (uint32_t)m << q;
        }
        miss = __reduce_or_sync(0xffffffffu, miss);
        if (tid == 0) TS(7);
#pragma unroll
        for (int q = NPRE; q < FIXAT; q++) {
            mbar_wait(bbox + 16 * q, 0);
            box_mma(q, of[q]);
        }
        for (unsigned it = 0;; it++) {
            if (miss) {
                uint32_t still = 0;
#pragma unroll
                for (int q = 0; q < 8; q++)
                    if (miss >> q & 1) {
                        uint4 d;
                        d.x = of[q].x ? 0u : nx[q].x; d.y = of[q].y ? 0u : nx[q].y; d.z = of[q].z ? 0u : nx[q].z; d.w = of[q].w ? 0u : nx[q].w;
                        of[q].x |= d.x; of[q].y |= d.y; of[q].z |= d.z; of[q].w |= d.w;
                        const bool m = !all_set(of[q]);
                        if (m) nx[q] = ld_word4(osrc + q * 8 * 128);
                        still |= (uint32_t)m << q;
                        __syncwarp();
                        if (q < FIXAT || it) box_mma(q, d);
                    }
                miss = __reduce_or_sync(0xffffffffu, still);
            }
            if (it == 0) {
#pragma unroll
                for (int q = FIXAT; q < 8; q++) {
                    mbar_wait(bbox + 16 * q, 0);
                    if (tid == 128 && q == 7) TS(12);
                    box_mma(q, of[q]);
                }
            }
            if (!miss) break;
            if (it > SPIN_LIMIT) __trap();
        }
        float* fred = reinterpret_cast<float*>(sp + OFF_S);
        {
            float* d = fred + (warp * 2 + (t >> 1)) * 80 + (t & 1) * 40 + g;
            const bool hf = t >> 1;
            d[0] = hf ? c[2][0] + c[3][0] : c[0][0] + c[1][0];
            d[20] = hf ? c[2][1] + c[3][1] : c[0][1] + c[1][1];
            d[8] = hf ? c[2][2] + c[3][2] : c[0][2] + c[1][2];
            d[28] = hf ? c[2][3] + c[3][3] : c[0][3] + c[1][3];
        }
        bar_sync(1, 256);
        if (tid < 64) {
            const float* s = fred + (tid >> 4) * 20 + (tid & 15);
            float v[16];
#pragma unroll
            for (int i = 0; i < 16; i++) v[i] = s[i * 80];
            const float acc = (((v[0] + v[1]) + (v[2] + v[3])) + ((v[4] + v[5]) + (v[6] + v[7]))) +
                              (((v[8] + v[9]) + (v[10] + v[11])) + ((v[12] + v[13]) + (v[14] + v[15])));
            asm volatile("st.global.u16 [%0], %1;" :: "l"(dst), "h"(__bfloat16_as_ushort(__float2bfloat16_rn(acc))) : "memory");
        }
        if (tid == 0) TS(9);
    }
}

__device__ float g_fb_q[2 * NB * HQ * DH];
__device__ float g_fb_o[2 * NB * HQ * DH];

struct Ptrs { const __nv_bfloat16 *x[2], *k[2], *v[2], *wq[2], *wo[2]; };

__global__ void fb_qproj(Ptrs p) {
    const int idx = blockIdx.x * blockDim.x + threadIdx.x;
    const int br = idx >> 14, b = (idx >> 12) & 3, col = idx & 4095;
    float acc = 0.f;
    for (int k = 0; k < DM; k++) acc += __bfloat162float(p.x[br][b * DM + k]) * __bfloat162float(p.wq[br][k * 4096 + col]);
    g_fb_q[idx] = bf16r(acc);
}
__global__ void fb_attn(Ptrs p) {
    __shared__ float s[WIN]; __shared__ float q[DH]; __shared__ float red[128];
    const int br = blockIdx.x >> 7, b = (blockIdx.x >> 5) & 3, h = blockIdx.x & 31, tid = threadIdx.x;
    const size_t base = ((size_t)(b * HKV + (h >> 1)) * SK + (SK - WIN)) * DH;
    q[tid] = g_fb_q[blockIdx.x * DH + tid];
    __syncthreads();
    float m = -INFINITY;
    for (int k = tid; k < WIN; k += 128) {
        float acc = 0.f;
        for (int d = 0; d < DH; d++) acc += q[d] * __bfloat162float(p.k[br][base + (size_t)k * DH + d]);
        acc = bf16r(bf16r(acc) * 0.08838834764831845f);
        s[k] = acc; m = fmaxf(m, acc);
    }
    red[tid] = m; __syncthreads();
    for (int i = 0; i < 128; i++) m = fmaxf(m, red[i]);
    __syncthreads();
    float sum = 0.f;
    for (int k = tid; k < WIN; k += 128) { float e = __expf(s[k] - m); s[k] = e; sum += e; }
    red[tid] = sum; __syncthreads();
    sum = 0.f;
    for (int i = 0; i < 128; i++) sum += red[i];
    const float inv = 1.0f / sum;
    float acc = 0.f;
    for (int k = 0; k < WIN; k++) acc += bf16r(s[k] * inv) * __bfloat162float(p.v[br][base + (size_t)k * DH + tid]);
    g_fb_o[blockIdx.x * DH + tid] = bf16r(acc);
}
__global__ void fb_oproj(Ptrs p, __nv_bfloat16* out) {
    const int idx = blockIdx.x * blockDim.x + threadIdx.x;
    if (idx >= NB * 2 * DM) return;
    const int b = idx / (2 * DM), c = idx % (2 * DM), br = c / DM, col = c % DM;
    float acc = 0.f;
    for (int k = 0; k < HQ * DH; k++) acc += g_fb_o[(br * NB + b) * HQ * DH + k] * __bfloat162float(p.wo[br][k * DM + col]);
    out[idx] = __float2bfloat16_rn(acc);
}

typedef CUresult (*EncodeFn)(CUtensorMap*, CUtensorMapDataType, cuuint32_t, void*, const cuuint64_t*, const cuuint64_t*,
                             const cuuint32_t*, const cuuint32_t*, CUtensorMapInterleave, CUtensorMapSwizzle,
                             CUtensorMapL2promotion, CUtensorMapFloatOOBfill);

bool encode_maps(Maps& m, void* const* d_in) {
    void* fn = nullptr;
    cudaDriverEntryPointQueryResult qr;
    if (cudaGetDriverEntryPoint("cuTensorMapEncodeTiled", &fn, cudaEnableDefault, &qr) != cudaSuccess || !fn) return false;
    EncodeFn enc = (EncodeFn)fn;
    const cuuint32_t es[3] = {1, 1, 1};
    bool ok = true;
    for (int br = 0; br < 2; br++) {
        {
            const cuuint64_t dims[2] = {64, (cuuint64_t)NB * HKV * SK * 2}, str[1] = {128};
            const cuuint32_t box[2] = {64, TILE_KEYS * 2 / SUB};
            ok &= enc(&m.k[br], CU_TENSOR_MAP_DATA_TYPE_BFLOAT16, 2, d_in[br * 5 + 1], dims, str, box, es, CU_TENSOR_MAP_INTERLEAVE_NONE,
                      CU_TENSOR_MAP_SWIZZLE_128B, CU_TENSOR_MAP_L2_PROMOTION_L2_256B, CU_TENSOR_MAP_FLOAT_OOB_FILL_NONE) == CUDA_SUCCESS;
            ok &= enc(&m.v[br], CU_TENSOR_MAP_DATA_TYPE_BFLOAT16, 2, d_in[br * 5 + 2], dims, str, box, es, CU_TENSOR_MAP_INTERLEAVE_NONE,
                      CU_TENSOR_MAP_SWIZZLE_128B, CU_TENSOR_MAP_L2_PROMOTION_L2_256B, CU_TENSOR_MAP_FLOAT_OOB_FILL_NONE) == CUDA_SUCCESS;
        }
        {
            const cuuint64_t dims[2] = {(cuuint64_t)HQ * DH, DM}, str[1] = {(cuuint64_t)HQ * DH * 2};
            const cuuint32_t box[2] = {64, 192};
            ok &= enc(&m.wq[br], CU_TENSOR_MAP_DATA_TYPE_BFLOAT16, 2, d_in[br * 5 + 3], dims, str, box, es, CU_TENSOR_MAP_INTERLEAVE_NONE,
                      CU_TENSOR_MAP_SWIZZLE_128B, CU_TENSOR_MAP_L2_PROMOTION_NONE, CU_TENSOR_MAP_FLOAT_OOB_FILL_NONE) == CUDA_SUCCESS;
        }
        {
            const cuuint64_t dims[2] = {DM, (cuuint64_t)HQ * DH}, str[1] = {DM * 2};
            const cuuint32_t box[2] = {16, 256};
            ok &= enc(&m.wo[br], CU_TENSOR_MAP_DATA_TYPE_BFLOAT16, 2, d_in[br * 5 + 4], dims, str, box, es, CU_TENSOR_MAP_INTERLEAVE_NONE,
                      CU_TENSOR_MAP_SWIZZLE_32B, WOPROMO, CU_TENSOR_MAP_FLOAT_OOB_FILL_NONE) == CUDA_SUCCESS;
        }
    }
    return ok;
}

}

static int g_tau = (int)(1310.0 / 32768.0 * 1048576.0), g_delta = 700, g_lead = 1800, g_taper = 900, g_ptaper = 9, g_ostep = 4608;

extern "C" void kernel_launch(void* const* d_in, const int* in_sizes, int n_in, void* d_out, int out_size) {
    (void)in_sizes; (void)n_in; (void)out_size;
    static int fast_ok = -1;
    if (fast_ok < 0) {
        int dev = 0, sms = 0, nb = 0;
        bool ok = cudaGetDevice(&dev) == cudaSuccess &&
                  cudaDeviceGetAttribute(&sms, cudaDevAttrMultiProcessorCount, dev) == cudaSuccess &&
                  cudaFuncSetAttribute(fused_decode_kernel, cudaFuncAttributeMaxDynamicSharedMemorySize, SMEM_BYTES) == cudaSuccess &&
                  cudaOccupancyMaxActiveBlocksPerMultiprocessor(&nb, fused_decode_kernel, NTHREADS, SMEM_BYTES) == cudaSuccess &&
                  sms * nb >= NCTA;
        fast_ok = ok ? 1 : 0;
        (void)cudaGetLastError();
    }
    Maps maps;
    if (fast_ok == 1 && encode_maps(maps, d_in)) {
        fused_decode_kernel<<<NCTA, NTHREADS, SMEM_BYTES>>>((const __nv_bfloat16*)d_in[0], (const __nv_bfloat16*)d_in[5],
                                                           (__nv_bfloat16*)d_out, g_tau, g_delta, g_lead, g_taper, g_ptaper, g_ostep, maps);
        return;
    }
    Ptrs p;
    for (int br = 0; br < 2; br++) {
        p.x[br] = (const __nv_bfloat16*)d_in[br * 5 + 0]; p.k[br] = (const __nv_bfloat16*)d_in[br * 5 + 1];
        p.v[br] = (const __nv_bfloat16*)d_in[br * 5 + 2]; p.wq[br] = (const __nv_bfloat16*)d_in[br * 5 + 3];
        p.wo[br] = (const __nv_bfloat16*)d_in[br * 5 + 4];
    }
    fb_qproj<<<2 * NB * HQ * DH / 256, 256>>>(p);
    fb_attn<<<2 * NB * HQ, 128>>>(p);
    fb_oproj<<<(NB * 2 * DM + 127) / 128, 128>>>(p, (__nv_bfloat16*)d_out);
}
```

```cpp
#include <cuda_runtime.h>
#include <cuda_bf16.h>
#include <cuda.h>
#include <stdint.h>

namespace {

constexpr int NB = 4, DM = 576, HQ = 32, HKV = 16, SK = 8192, DH = 128, WIN = 2048;
constexpr int NCTA = 128;
constexpr int NST = 4;
constexpr int SUB = 2;
constexpr int NWQ = 3;
constexpr int NPRE = 5;
constexpr int REP_FIRST = 5, REP_LAST = 29;
constexpr int TILE_KEYS = 128;
constexpr int STAGE_BYTES = TILE_KEYS * DH * 2;
constexpr int NTILE = WIN / TILE_KEYS;
constexpr int WBUF_BYTES = 73728;
constexpr int NOWN = DM / 16;
constexpr int NWO = HKV;
constexpr int WO_BOX_BYTES = 256 * 32;
constexpr int WO_STEP = WBUF_BYTES / NWO;
constexpr int XPITCH = 1168;

constexpr int OFF_STAGE = 0;
constexpr int OFF_WBUF = OFF_STAGE + NST * STAGE_BYTES;
constexpr int OFF_S = OFF_WBUF + WBUF_BYTES;
constexpr int OFF_WO = OFF_S - NWO * WO_BOX_BYTES;
constexpr int OFF_Q = OFF_S + 16384;
constexpr int OFF_ORED = OFF_Q + 512;
constexpr int OFF_RED = OFF_ORED + 2 * 288 * 4;
constexpr int OFF_CTL = OFF_RED + 128;
constexpr int OFF_BAR = OFF_CTL + 16;
constexpr int SMEM_USED = OFF_BAR + 448;
constexpr int SMEM_BYTES = SMEM_USED + 1024;

constexpr int NTHREADS = 352;
constexpr unsigned SPIN_LIMIT = 1u << 24;

struct Maps { CUtensorMap k[2], v[2], wq[2], wo[2]; };

__device__ __align__(128) unsigned long long g_qx[NCTA * 128];
__device__ __align__(128) uint32_t g_ox[NCTA * 128];
__device__ __align__(128) unsigned int g_ready[32];
__device__ __align__(128) unsigned int g_epoch[NCTA * 32];
__device__ __align__(128) unsigned long long g_prog[2 * NTILE * 16];

__device__ __forceinline__ uint32_t gtime32() { uint32_t t; asm volatile("mov.u32 %0, %%globaltimer_lo;" : "=r"(t)); return t; }

__device__ __forceinline__ uint32_t smem_u32(const void* p) { return (uint32_t)__cvta_generic_to_shared(p); }
__device__ __forceinline__ void mbar_init(uint32_t a, uint32_t c) { asm volatile("mbarrier.init.shared::cta.b64 [%0], %1;" :: "r"(a), "r"(c) : "memory"); }
__device__ __forceinline__ void mbar_expect_tx(uint32_t a, uint32_t b) { asm volatile("mbarrier.arrive.expect_tx.shared::cta.b64 _, [%0], %1;" :: "r"(a), "r"(b) : "memory"); }
__device__ __forceinline__ void mbar_arrive(uint32_t a) { asm volatile("mbarrier.arrive.shared::cta.b64 _, [%0];" :: "r"(a) : "memory"); }
__device__ __forceinline__ bool mbar_try(uint32_t a, uint32_t ph) {
    uint32_t ok;
    asm volatile("{\n.reg .pred p;\nmbarrier.try_wait.parity.shared::cta.b64 p, [%1], %2;\nselp.u32 %0, 1, 0, p;\n}"
                 : "=r"(ok) : "r"(a), "r"(ph) : "memory");
    return ok != 0;
}
__device__ __forceinline__ void mbar_wait(uint32_t a, uint32_t ph) {
    uint32_t ok; unsigned it = 0;
    do {
        asm volatile("{\n.reg .pred p;\nmbarrier.try_wait.parity.shared::cta.b64 p, [%1], %2;\nselp.u32 %0, 1, 0, p;\n}"
                     : "=r"(ok) : "r"(a), "r"(ph) : "memory");
        if (++it > SPIN_LIMIT) __trap();
    } while (!ok);
}
__device__ __forceinline__ bool mbar_test(uint32_t a, uint32_t ph) {
    uint32_t ok;
    asm volatile("{\n.reg .pred p;\nmbarrier.test_wait.parity.shared::cta.b64 p, [%1], %2;\nselp.u32 %0, 1, 0, p;\n}"
                 : "=r"(ok) : "r"(a), "r"(ph) : "memory");
    return ok != 0;
}
__device__ __forceinline__ void bulk_g2s(uint32_t dst, const void* src, uint32_t bytes, uint32_t bar) {
    asm volatile("cp.async.bulk.shared::cluster.global.mbarrier::complete_tx::bytes [%0], [%1], %2, [%3];"
                 :: "r"(dst), "l"(src), "r"(bytes), "r"(bar) : "memory");
}
__device__ __forceinline__ void tma2d(uint32_t dst, const CUtensorMap* m, int c0, int c1, uint32_t bar, uint64_t pol) {
    asm volatile("cp.async.bulk.tensor.2d.shared::cluster.global.mbarrier::complete_tx::bytes.L2::cache_hint [%0], [%1, {%3, %4}], [%2], %5;"
                 :: "r"(dst), "l"(m), "r"(bar), "r"(c0), "r"(c1), "l"(pol) : "memory");
}
__device__ __forceinline__ void tma2d_nohint(uint32_t dst, const CUtensorMap* m, int c0, int c1, uint32_t bar) {
    asm volatile("cp.async.bulk.tensor.2d.shared::cluster.global.mbarrier::complete_tx::bytes [%0], [%1, {%3, %4}], [%2];"
                 :: "r"(dst), "l"(m), "r"(bar), "r"(c0), "r"(c1) : "memory");
}
__device__ __forceinline__ void ldsm4(uint32_t (&r)[4], uint32_t a) {
    asm volatile("ldmatrix.sync.aligned.m8n8.x4.shared.b16 {%0,%1,%2,%3}, [%4];"
                 : "=r"(r[0]), "=r"(r[1]), "=r"(r[2]), "=r"(r[3]) : "r"(a));
}
__device__ __forceinline__ void ldsm4t(uint32_t (&r)[4], uint32_t a) {
    asm volatile("ldmatrix.sync.aligned.m8n8.x4.trans.shared.b16 {%0,%1,%2,%3}, [%4];"
                 : "=r"(r[0]), "=r"(r[1]), "=r"(r[2]), "=r"(r[3]) : "r"(a));
}
__device__ __forceinline__ void mma16816(float (&c)[4], const uint32_t (&a)[4], uint32_t b0, uint32_t b1) {
    asm("mma.sync.aligned.m16n8k16.row.col.f32.bf16.bf16.f32 {%0,%1,%2,%3}, {%4,%5,%6,%7}, {%8,%9}, {%0,%1,%2,%3};"
                 : "+f"(c[0]), "+f"(c[1]), "+f"(c[2]), "+f"(c[3])
                 : "r"(a[0]), "r"(a[1]), "r"(a[2]), "r"(a[3]), "r"(b0), "r"(b1));
}
__device__ __forceinline__ uint32_t lds32(uint32_t a) { uint32_t v; asm volatile("ld.shared.u32 %0, [%1];" : "=r"(v) : "r"(a)); return v; }
__device__ __forceinline__ void sts32(uint32_t a, float v) { asm volatile("st.shared.f32 [%0], %1;" :: "r"(a), "f"(v) : "memory"); }
__device__ __forceinline__ float4 lds128f(uint32_t a) {
    float4 v; asm volatile("ld.shared.v4.f32 {%0,%1,%2,%3}, [%4];" : "=f"(v.x), "=f"(v.y), "=f"(v.z), "=f"(v.w) : "r"(a) : "memory"); return v;
}
__device__ __forceinline__ void bar_sync(int id, int n) { asm volatile("bar.sync %0, %1;" :: "r"(id), "r"(n) : "memory"); }

__device__ __forceinline__ void st_word(uint32_t* p, uint32_t w) { asm volatile("st.relaxed.gpu.global.u32 [%0], %1;" :: "l"(p), "r"(w) : "memory"); }
__device__ __forceinline__ void st_u64(unsigned long long* p, unsigned long long w) { asm volatile("st.relaxed.gpu.global.u64 [%0], %1;" :: "l"(p), "l"(w) : "memory"); }
__device__ __forceinline__ void st_zero4(uint32_t* p) { asm volatile("st.relaxed.gpu.global.v4.u32 [%0], {%1, %1, %1, %1};" :: "l"(p), "r"(0u) : "memory"); }
__device__ __forceinline__ uint4 ld_word4(const uint32_t* p) {
    uint4 v;
    asm volatile("ld.relaxed.gpu.global.v4.u32 {%0, %1, %2, %3}, [%4];" : "=r"(v.x), "=r"(v.y), "=r"(v.z), "=r"(v.w) : "l"(p) : "memory");
    return v;
}
__device__ __forceinline__ bool all_set(const uint4& v) { return min(min(v.x, v.y), min(v.z, v.w)) != 0u; }
__device__ __forceinline__ unsigned long long ld_u64(const unsigned long long* p) {
    unsigned long long w;
    asm volatile("ld.relaxed.gpu.global.u64 %0, [%1];" : "=l"(w) : "l"(p) : "memory");
    return w;
}
__device__ __forceinline__ void ld_u64x2(const unsigned long long* p, unsigned long long& w0, unsigned long long& w1) {
    asm volatile("ld.relaxed.gpu.global.v2.u64 {%0, %1}, [%2];" : "=l"(w0), "=l"(w1) : "l"(p) : "memory");
}
__device__ __forceinline__ void st_zero2(unsigned long long* p) { asm volatile("st.relaxed.gpu.global.v2.u64 [%0], {%1, %1};" :: "l"(p), "l"(0ull) : "memory"); }
__device__ __forceinline__ int tile_slot(int i) { return i < NST + 2 ? i : ((i - NST - 2) & (NST - 1)); }
__device__ __forceinline__ uint32_t tile_par(int i) { return i < NST + 2 ? 0u : (uint32_t)((1 + ((i - NST - 2) >> 2)) & 1); }
__device__ __forceinline__ int cum_bytes(int i) { return WBUF_BYTES + i * STAGE_BYTES; }
__device__ __forceinline__ void pace(uint32_t t_start, int bytes, int tau, const volatile int* offset) {
    const int due = (int)(((long long)bytes * tau) >> 20);
    while ((int)(gtime32() - t_start) < due + *offset) {}
}
__device__ __forceinline__ float bf16r(float v) { return __bfloat162float(__float2bfloat16_rn(v)); }
__device__ __forceinline__ uint32_t pack_bf16(float lo, float hi) {
    __nv_bfloat162 t = __floats2bfloat162_rn(lo, hi);
    return *reinterpret_cast<uint32_t*>(&t);
}

__global__ void __launch_bounds__(NTHREADS, 1)
fused_decode_kernel(const __nv_bfloat16* __restrict__ xA, const __nv_bfloat16* __restrict__ xB, __nv_bfloat16* __restrict__ out,
                    int tau, int delta, int lead, int taper, int ow, int ostep,
                    const __grid_constant__ Maps maps) {
    extern __shared__ unsigned char smem_raw[];
    const uint32_t sb = (smem_u32(smem_raw) + 1023u) & ~1023u;
    unsigned char* sp = smem_raw + (sb - smem_u32(smem_raw));

    const int tid = threadIdx.x, warp = tid >> 5, lane = tid & 31;
    const int g = lane >> 2, t = lane & 3;
    const int cta = blockIdx.x;
    const int br = cta >> 6, hkv = (cta >> 2) & 15, r = cta & 3;
    const int strip = !(cta & 1) ? (cta & 63) >> 1 : (cta & 15) == 1 ? 32 + ((cta & 63) >> 4) : NOWN;

    const uint32_t bar_full = sb + OFF_BAR, bar_empty = bar_full + 8 * (NST + 2);
    const uint32_t bar_wq = bar_empty + 8 * NST, bar_wqfree = bar_wq + 72, bar_go = bar_wqfree + 8, bar_q = bar_go + 8, bar_rdy = bar_q + 8, bar_chk = bar_rdy + 8, bar_wo = bar_chk + 8;
    const int row0 = ((r * HKV + hkv) * SK + (SK - WIN)) * 2;

    uint64_t pol = 0;
    uint32_t t_start = 0;
    volatile int* ctl = reinterpret_cast<volatile int*>(sp + OFF_CTL);
    if (warp < NWQ && lane == 0) {
        mbar_init(bar_wq + 8 * warp, 1);
        asm volatile("fence.mbarrier_init.release.cluster;" ::: "memory");
        asm volatile("createpolicy.fractional.L2::evict_first.b64 %0, 1.0;" : "=l"(pol));
        mbar_expect_tx(bar_wq + 8 * warp, WBUF_BYTES / NWQ + (warp == 0 ? NB * DM * 2 : 0));
        tma2d(sb + OFF_WBUF + warp * (DM / NWQ) * 128, &maps.wq[br], hkv * 256 + r * 64, warp * (DM / NWQ), bar_wq + 8 * warp, pol);
        if (warp == 0) {
            const __nv_bfloat16* x = br ? xB : xA;
#pragma unroll
            for (int b = 0; b < NB; b++) bulk_g2s(sb + OFF_S + b * XPITCH, x + b * DM, DM * 2, bar_wq);
        }
    }
    if (tid == 256) {
        t_start = gtime32();
        asm volatile("createpolicy.fractional.L2::evict_first.b64 %0, 1.0;" : "=l"(pol));
        for (int i = 0; i < NST + 2; i++) mbar_init(bar_full + 8 * i, 1);
        for (int i = 0; i < NST; i++) mbar_init(bar_empty + 8 * i, 8);
        ctl[0] = -delta; ctl[1] = (int)t_start;
        mbar_init(bar_wqfree, 4);
        mbar_init(bar_go, 1);
        mbar_init(bar_q, 1);
        mbar_init(bar_rdy, 2);
        mbar_init(bar_chk, 1);
        for (int i = 0; i < NWO; i++) mbar_init(bar_wo + 8 * i, 1);
        asm volatile("fence.mbarrier_init.release.cluster;" ::: "memory");
        for (int i = 0; i < NWO; i++) mbar_expect_tx(bar_wo + 8 * i, WO_BOX_BYTES);
    }
    uint32_t epoch;
    asm volatile("ld.relaxed.gpu.global.u32 %0, [%1];" : "=r"(epoch) : "l"(&g_epoch[cta * 32 + lane]) : "memory");
    if (warp == 10) st_zero4(&g_ox[cta * 128 + lane * 4]);
    if (warp == 4 || warp == 5) st_zero2(&g_qx[((cta & ~3) + ((tid - 128) >> 4)) * 128 + r * 32 + (lane & 15) * 2]);
    if (warp == 6 && cta < 2 * NTILE && lane < 8) st_zero2(&g_prog[cta * 16 + lane * 2]);
    __syncthreads();

    if (warp == 9) {
        mbar_wait(bar_wqfree, 0);
        epoch += 1u;
        const unsigned long long* qsrc = &g_qx[cta * 128 + lane * 4];
        unsigned long long u0, u1, u2, u3;
        for (unsigned it = 0;; it++) {
            ld_u64x2(qsrc, u0, u1); ld_u64x2(qsrc + 2, u2, u3);
            if ((uint32_t)(u0 >> 32) == epoch && (uint32_t)(u1 >> 32) == epoch && (uint32_t)(u2 >> 32) == epoch && (uint32_t)(u3 >> 32) == epoch) break;
            if (it > SPIN_LIMIT) __trap();
            __nanosleep(100);
        }
        const uint4 w = make_uint4((uint32_t)u0, (uint32_t)u1, (uint32_t)u2, (uint32_t)u3);
        uint2* qs = reinterpret_cast<uint2*>(sp + OFF_Q + (lane >> 1) * 32 + (lane & 1) * 8);
        qs[0] = make_uint2(__byte_perm(w.x, w.y, 0x5410), __byte_perm(w.z, w.w, 0x5410));
        qs[2] = make_uint2(__byte_perm(w.x, w.y, 0x7632), __byte_perm(w.z, w.w, 0x7632));
        __syncwarp();
        if (lane == 0) {
            mbar_arrive(bar_q);
            for (unsigned it = 0;; it++) {
                unsigned v;
                asm volatile("ld.acquire.gpu.global.u32 %0, [%1];" : "=r"(v) : "l"(g_ready) : "memory");
                if ((int)(v - epoch * NCTA) >= 0) break;
                if (it > SPIN_LIMIT) __trap();
                __nanosleep(200);
            }
            mbar_arrive(bar_rdy);
            mbar_arrive(bar_chk);
            unsigned long long* prog = g_prog;
            const uint32_t t0 = (uint32_t)ctl[1];
            for (int i = REP_FIRST; i <= REP_LAST; i++) {
                while (!mbar_try(bar_full + 8 * tile_slot(i), tile_par(i)))
                    if (mbar_test(bar_go, 0)) return;
                const unsigned long long v = (1ull << 40) | (unsigned long long)min(gtime32() - t0, 1u << 24);
                asm volatile("red.relaxed.gpu.global.add.u64 [%0], %1;" :: "l"(prog + i * 16), "l"(v) : "memory");
            }
        }
        return;
    }
    if (warp == 10) {
        if (lane == 0) asm volatile("red.release.gpu.global.add.u32 [%0], %1;" :: "l"(g_ready), "r"(1u) : "memory");
        mbar_wait(bar_q, 0);
        epoch += 1u;
        g_epoch[cta * 32 + lane] = epoch;
        if (lane == 0) {
            const unsigned long long* prog = g_prog;
            mbar_wait(bar_full + 8 * tile_slot(REP_FIRST - 1), tile_par(REP_FIRST - 1));
            mbar_wait(bar_chk, 0);
            int n = REP_FIRST;
            for (unsigned it = 0; n <= REP_LAST && it < SPIN_LIMIT && !mbar_test(bar_go, 0); it++) {
                unsigned long long w = ld_u64(prog + n * 16);
                const unsigned long long w1 = ld_u64(prog + (n + 1) * 16);
                if ((w1 >> 40) == NCTA) { w = w1; n++; }
                if ((w >> 40) == NCTA) {
                    const int avg = (int)((w & ((1ull << 40) - 1)) / NCTA);
                    const int off = avg - (int)(((long long)cum_bytes(n + 1) * tau) >> 20) - lead;
                    ctl[0] = max(-delta - 4000, min(off, 8000));
                    n++;
                } else {
                    __nanosleep(200);
                }
            }
        }
        return;
    }
    if (warp == 8) {
        if (lane == 0) {
            for (int i = 0; i < 2 * NTILE; i++) {
                const int slot = tile_slot(i);
                if (i >= NST + 2) mbar_wait(bar_empty + 8 * slot, tile_par(i) ^ 1);
                else if (i == NST) mbar_wait(bar_wqfree, 0);
                const CUtensorMap* m = (i < NTILE) ? &maps.k[br] : &maps.v[br];
#pragma unroll
                for (int sub = 0; sub < SUB; sub++) {
                    pace(t_start, cum_bytes(i) + sub * (STAGE_BYTES / SUB), tau, ctl);
                    if (sub == 0) mbar_expect_tx(bar_full + 8 * slot, STAGE_BYTES);
                    tma2d(sb + OFF_STAGE + slot * STAGE_BYTES + sub * (STAGE_BYTES / SUB), m, 0,
                          row0 + (i & (NTILE - 1)) * TILE_KEYS * 2 + sub * (TILE_KEYS * 2 / SUB), bar_full + 8 * slot, pol);
                }
            }
            mbar_arrive(bar_go);
            if (strip < NOWN) {
                mbar_wait(bar_empty + 8 * tile_slot(2 * NTILE), tile_par(2 * NTILE) ^ 1);
                mbar_wait(bar_empty + 8 * tile_slot(2 * NTILE + 1), tile_par(2 * NTILE + 1) ^ 1);
                uint32_t due = t_start + taper + ctl[0] + (int)(((long long)cum_bytes(2 * NTILE) * tau) >> 20);
                const uint32_t step = (uint32_t)(((long long)ostep * tau) >> 20);
                const CUtensorMap* m = &maps.wo[br];
#pragma unroll 1
                for (int i = 0; i < NWO; i++, due += step) {
                    while ((int)(gtime32() - due) < 0) {}
                    tma2d_nohint(sb + OFF_WO + i * WO_BOX_BYTES, m, strip * 16, i * 256, bar_wo + 8 * i);
                    if (i == ow) mbar_arrive(bar_rdy);
                }
            }
        }
        return;
    }
    {
        if (warp < 4) {
            mbar_wait(bar_wq, 0); mbar_wait(bar_wq + 8, 0);
            for (int j = 2; j < NWQ; j++) mbar_wait(bar_wq + 8 * j, 0);
            float c0[4] = {0.f, 0.f, 0.f, 0.f}, c1[4] = {0.f, 0.f, 0.f, 0.f};
            const int mi = lane >> 3, i8 = lane & 7;
            const uint32_t abase = sb + OFF_WBUF + (i8 + 8 * (mi >> 1)) * 128 + (((2 * warp + (mi & 1)) ^ i8) << 4);
            const uint32_t xb = sb + OFF_S + (g & 3) * XPITCH + t * 4;
#pragma unroll 6
            for (int ks = 0; ks < 36; ks += 2) {
                uint32_t a[4], a2[4];
                ldsm4t(a, abase + ks * 2048);
                ldsm4t(a2, abase + ks * 2048 + 2048);
                uint32_t b0 = lds32(xb + ks * 32), b1 = lds32(xb + ks * 32 + 16);
                uint32_t b2 = lds32(xb + ks * 32 + 32), b3 = lds32(xb + ks * 32 + 48);
                mma16816(c0, a, b0, b1);
                mma16816(c1, a2, b2, b3);
            }
            __syncwarp();
            if (lane == 0) mbar_arrive(bar_wqfree);
            epoch += 1u;
            if (t < 2) {
#pragma unroll
                for (int e = 0; e < 2; e++)
                    st_u64(&g_qx[((cta & ~3) + 2 * t + e) * 128 + r * 32 + warp * 8 + g],
                           ((unsigned long long)epoch << 32) | pack_bf16(c0[e] + c1[e], c0[2 + e] + c1[2 + e]));
            }
        }
        mbar_wait(bar_q, 0);

        {
            uint32_t qb[2][4][2];
            const int h = g & 1, sel = (g >> 1) & 1;
#pragma unroll
            for (int p = 0; p < 2; p++)
#pragma unroll
                for (int s = 0; s < 4; s++) {
                    const uint32_t a = sb + OFF_Q + (h * 128 + ((sel ^ p) * 64) + s * 16 + 2 * t) * 2;
                    qb[p][s][0] = lds32(a);
                    qb[p][s][1] = lds32(a + 16);
                }
            const int mi = lane >> 3, i8 = lane & 7;
            const int key = warp * 16 + i8 + 8 * (mi & 1);
            uint32_t koff[2];
#pragma unroll
            for (int p = 0; p < 2; p++) {
                const int j = 2 * key + ((i8 >> 2) ^ p);
                koff[p] = j * 128 + (((mi >> 1) ^ (j & 7)) << 4);
            }
            float2* S = reinterpret_cast<float2*>(sp + OFF_S);
            const bool valid = (t == (g >> 2));
            const float scale = 0.08838834764831845f;
#pragma unroll 1
            for (int it = 0; it < NTILE; it++) {
                const int st = tile_slot(it);
                mbar_wait(bar_full + 8 * st, tile_par(it));
                const uint32_t base = sb + OFF_STAGE + st * STAGE_BYTES;
                float ca[4] = {0.f, 0.f, 0.f, 0.f}, cb[4] = {0.f, 0.f, 0.f, 0.f};
#pragma unroll
                for (int s = 0; s < 4; s++) {
                    uint32_t a[4], a2[4];
                    ldsm4(a, base + (koff[0] ^ (s << 5)));
                    ldsm4(a2, base + (koff[1] ^ (s << 5)));
                    mma16816(ca, a, qb[0][s][0], qb[0][s][1]);
                    mma16816(cb, a2, qb[1][s][0], qb[1][s][1]);
                }
                __syncwarp();
                if (lane == 0 && st < NST) mbar_arrive(bar_empty + 8 * st);
                const float2 s0 = make_float2(bf16r(bf16r(ca[0] + cb[0]) * scale), bf16r(bf16r(ca[1] + cb[1]) * scale));
                const float2 s1 = make_float2(bf16r(bf16r(ca[2] + cb[2]) * scale), bf16r(bf16r(ca[3] + cb[3]) * scale));
                if (valid) {
                    const int k0 = it * TILE_KEYS + warp * 16 + g;
                    S[k0] = s0;
                    S[k0 + 8] = s1;
                }
            }
            bar_sync(1, 256);
        }

        {
            const int gp = tid >> 2, tt = tid & 3;
            float4 sv[4];
#pragma unroll
            for (int j = 0; j < 4; j++)
                sv[j] = *reinterpret_cast<const float4*>(sp + OFF_S + (gp * 32 + j * 8 + 2 * tt) * 8);
            float m0 = -INFINITY, m1 = -INFINITY;
#pragma unroll
            for (int j = 0; j < 4; j++) {
                m0 = fmaxf(m0, fmaxf(sv[j].x, sv[j].z));
                m1 = fmaxf(m1, fmaxf(sv[j].y, sv[j].w));
            }
#pragma unroll
            for (int o = 16; o; o >>= 1) {
                m0 = fmaxf(m0, __shfl_xor_sync(0xffffffffu, m0, o));
                m1 = fmaxf(m1, __shfl_xor_sync(0xffffffffu, m1, o));
            }
            float2* red = reinterpret_cast<float2*>(sp + OFF_RED);
            if (lane == 0) red[warp] = make_float2(m0, m1);
            bar_sync(1, 256);
#pragma unroll
            for (int w = 0; w < 8; w++) { float2 v = red[w]; m0 = fmaxf(m0, v.x); m1 = fmaxf(m1, v.y); }
            float s0 = 0.f, s1 = 0.f;
#pragma unroll
            for (int j = 0; j < 4; j++) {
                sv[j].x = __expf(sv[j].x - m0); sv[j].z = __expf(sv[j].z - m0);
                sv[j].y = __expf(sv[j].y - m1); sv[j].w = __expf(sv[j].w - m1);
                s0 += sv[j].x + sv[j].z; s1 += sv[j].y + sv[j].w;
            }
#pragma unroll
            for (int o = 16; o; o >>= 1) {
                s0 += __shfl_xor_sync(0xffffffffu, s0, o);
                s1 += __shfl_xor_sync(0xffffffffu, s1, o);
            }
            if (lane == 0) red[8 + warp] = make_float2(s0, s1);
            bar_sync(1, 256);
            s0 = 0.f; s1 = 0.f;
#pragma unroll
            for (int w = 0; w < 8; w++) { float2 v = red[8 + w]; s0 += v.x; s1 += v.y; }
            const float i0 = 1.0f / s0, i1 = 1.0f / s1;
            uint4 p0, p1;
            p0.x = pack_bf16(sv[0].x * i0, sv[0].z * i0); p1.x = pack_bf16(sv[0].y * i1, sv[0].w * i1);
            p0.y = pack_bf16(sv[1].x * i0, sv[1].z * i0); p1.y = pack_bf16(sv[1].y * i1, sv[1].w * i1);
            p0.z = pack_bf16(sv[2].x * i0, sv[2].z * i0); p1.z = pack_bf16(sv[2].y * i1, sv[2].w * i1);
            p0.w = pack_bf16(sv[3].x * i0, sv[3].z * i0); p1.w = pack_bf16(sv[3].y * i1, sv[3].w * i1);
            *reinterpret_cast<uint4*>(sp + OFF_S + gp * 128 + tt * 16) = p0;
            *reinterpret_cast<uint4*>(sp + OFF_S + gp * 128 + 64 + tt * 16) = p1;
            bar_sync(1, 256);
        }

        {
            float oa[4] = {0.f, 0.f, 0.f, 0.f}, ob[4] = {0.f, 0.f, 0.f, 0.f};
            const int mt = warp & 3, p = warp >> 2;
            const int mi = lane >> 3, i8 = lane & 7;
            const int j = 2 * (i8 + 8 * (mi >> 1)) + ((i8 >> 2) ^ p);
            const uint32_t voff = j * 128 + (((2 * mt + (mi & 1)) ^ (j & 7)) << 4);
            const bool live = (g < 4) && (((g >> 1) & 1) == ((t >> 1) ^ p));
            const unsigned char* pp = sp + OFF_S + (g & 1) * 64 + t * 16;
#pragma unroll 1
            for (int it = 0; it < NTILE; it++) {
                uint4 pf[4];
#pragma unroll
                for (int q = 0; q < 4; q++) {
                    pf[q] = *reinterpret_cast<const uint4*>(pp + (it * 4 + q) * 128);
                    if (!live) pf[q] = make_uint4(0u, 0u, 0u, 0u);
                }
                const int st = tile_slot(NTILE + it);
                mbar_wait(bar_full + 8 * st, tile_par(NTILE + it));
                const uint32_t base = sb + OFF_STAGE + st * STAGE_BYTES + voff;
#pragma unroll
                for (int q = 0; q < 4; q++) {
                    uint32_t a[4], a2[4];
                    ldsm4t(a, base + q * 8192);
                    ldsm4t(a2, base + q * 8192 + 4096);
                    mma16816(oa, a, pf[q].x, pf[q].y);
                    mma16816(ob, a2, pf[q].z, pf[q].w);
                }
                __syncwarp();
                if (lane == 0) mbar_arrive(bar_empty + 8 * st);
            }
            float* ored = reinterpret_cast<float*>(sp + OFF_ORED);
            if (t < 2) {
                float* d = ored + p * 288 + 72 * t + 16 * mt + g;
                d[0] = oa[0] + ob[0]; d[144] = oa[1] + ob[1]; d[8] = oa[2] + ob[2]; d[152] = oa[3] + ob[3];
            }
            bar_sync(1, 256);
            if (warp < 4) {
                const float* s = ored + 72 * warp + 32 * (lane >> 4) + 8 * (lane & 3) + 2 * ((lane >> 2) & 3);
                const float2 u = *reinterpret_cast<const float2*>(s), v = *reinterpret_cast<const float2*>(s + 288);
                const uint32_t w = pack_bf16(u.x + v.x, u.y + v.y);
                st_word(&g_ox[cta * 128 + tid], w ? w : 0x8000u);
            }
        }
    }
    if (strip >= NOWN) return;

    {
        const int mi = lane >> 3, i8 = lane & 7, kg = warp & 3, bp = warp >> 2;
        const uint32_t abase = sb + OFF_WO + (64 * kg + i8 + 8 * (mi >> 1)) * 32 + (((mi & 1) ^ (i8 >> 2)) << 4);
        const uint32_t* osrc = &g_ox[(br * 64 + bp * 4 + (g & 3)) * 128 + kg * 32 + (g >> 2) * 16 + t * 4];
        uint32_t abox = abase + bp * WO_BOX_BYTES, bbox = bar_wo + 8 * bp;
        __nv_bfloat16* dst = out + ((tid >> 4) & 3) * (2 * DM) + br * DM + strip * 16 + (tid & 15);
        uint32_t wr = sb + OFF_S + (((t & 1) * 32 + g) * 20 + ((2 * warp + (t >> 1)) ^ (2 * (t & 1)))) * 4;
        uint32_t rd = tid < 64 ? sb + OFF_S + tid * 80 : 0u, hf = t >> 1;
        asm volatile("" : "+l"(osrc), "+r"(abox), "+r"(bbox), "+l"(dst), "+r"(wr), "+r"(rd), "+r"(hf));
        float c[4][4];
#pragma unroll
        for (int i = 0; i < 16; i++) (&c[0][0])[i] = 0.f;
        auto box_mma = [&](int q, const uint4& b) {
            uint32_t a[4][4];
#pragma unroll
            for (int s = 0; s < 4; s++) ldsm4t(a[s], abox + q * 2 * WO_BOX_BYTES + s * 512);
            mma16816(c[0], a[0], b.x, b.y);
            mma16816(c[1], a[1], b.z, b.w);
            mma16816(c[2], a[2], b.x, b.y);
            mma16816(c[3], a[3], b.z, b.w);
        };
        uint4 of[8], nx[8];
        mbar_wait(bar_rdy, 0);
#pragma unroll
        for (int q = 0; q < 8; q++) of[q] = ld_word4(osrc + q * 8 * 128);
        uint32_t af[NPRE][4][4];
#pragma unroll
        for (int q = 0; q < NPRE; q++) {
            mbar_wait(bbox + 16 * q, 0);
#pragma unroll
            for (int s = 0; s < 4; s++) ldsm4t(af[q][s], abox + q * 2 * WO_BOX_BYTES + s * 512);
        }
        uint32_t miss = 0;
#pragma unroll
        for (int q = 0; q < NPRE; q++) {
            mma16816(c[0], af[q][0], of[q].x, of[q].y);
            mma16816(c[1], af[q][1], of[q].z, of[q].w);
            mma16816(c[2], af[q][2], of[q].x, of[q].y);
            mma16816(c[3], af[q][3], of[q].z, of[q].w);
        }
#pragma unroll
        for (int q = 0; q < 8; q++) {
            const bool m = !all_set(of[q]);
            if (m) nx[q] = ld_word4(osrc + q * 8 * 128);
            miss |= (uint32_t)m << q;
        }
        miss = __reduce_or_sync(0xffffffffu, miss);
#pragma unroll
        for (int q = NPRE; q < 7; q++) {
            mbar_wait(bbox + 16 * q, 0);
            box_mma(q, of[q]);
        }
        for (unsigned it = 0;; it++) {
            if (miss) {
                uint32_t still = 0;
#pragma unroll
                for (int q = 0; q < 8; q++)
                    if (miss >> q & 1) {
                        uint4 d;
                        d.x = of[q].x ? 0u : nx[q].x; d.y = of[q].y ? 0u : nx[q].y; d.z = of[q].z ? 0u : nx[q].z; d.w = of[q].w ? 0u : nx[q].w;
                        of[q].x |= d.x; of[q].y |= d.y; of[q].z |= d.z; of[q].w |= d.w;
                        const bool m = !all_set(of[q]);
                        if (m) nx[q] = ld_word4(osrc + q * 8 * 128);
                        still |= (uint32_t)m << q;
                        __syncwarp();
                        if (q < 7 || it) box_mma(q, d);
                    }
                miss = __reduce_or_sync(0xffffffffu, still);
            }
            if (it == 0) {
#pragma unroll
                for (int q = 7; q < 8; q++) {
                    mbar_wait(bbox + 16 * q, 0);
                    box_mma(q, of[q]);
                }
            }
            if (!miss) break;
            if (it > SPIN_LIMIT) __trap();
        }
        sts32(wr, hf ? c[2][0] + c[3][0] : c[0][0] + c[1][0]);
        sts32(wr + 16 * 80, hf ? c[2][1] + c[3][1] : c[0][1] + c[1][1]);
        sts32(wr + 8 * 80, hf ? c[2][2] + c[3][2] : c[0][2] + c[1][2]);
        sts32(wr + 24 * 80, hf ? c[2][3] + c[3][3] : c[0][3] + c[1][3]);
        bar_sync(1, 256);
        if (rd) {
            const float4 v0 = lds128f(rd), v1 = lds128f(rd + 16), v2 = lds128f(rd + 32), v3 = lds128f(rd + 48);
            const float acc = (((v0.x + v0.y) + (v0.z + v0.w)) + ((v1.x + v1.y) + (v1.z + v1.w))) +
                              (((v2.x + v2.y) + (v2.z + v2.w)) + ((v3.x + v3.y) + (v3.z + v3.w)));
            asm volatile("st.global.u16 [%0], %1;" :: "l"(dst), "h"(__bfloat16_as_ushort(__float2bfloat16_rn(acc))) : "memory");
        }
    }
}

__device__ float g_fb_q[2 * NB * HQ * DH];
__device__ float g_fb_o[2 * NB * HQ * DH];

struct Ptrs { const __nv_bfloat16 *x[2], *k[2], *v[2], *wq[2], *wo[2]; };

__global__ void fb_qproj(Ptrs p) {
    const int idx = blockIdx.x * blockDim.x + threadIdx.x;
    const int br = idx >> 14, b = (idx >> 12) & 3, col = idx & 4095;
    float acc = 0.f;
    for (int k = 0; k < DM; k++) acc += __bfloat162float(p.x[br][b * DM + k]) * __bfloat162float(p.wq[br][k * 4096 + col]);
    g_fb_q[idx] = bf16r(acc);
}
__global__ void fb_attn(Ptrs p) {
    __shared__ float s[WIN]; __shared__ float q[DH]; __shared__ float red[128];
    const int br = blockIdx.x >> 7, b = (blockIdx.x >> 5) & 3, h = blockIdx.x & 31, tid = threadIdx.x;
    const size_t base = ((size_t)(b * HKV + (h >> 1)) * SK + (SK - WIN)) * DH;
    q[tid] = g_fb_q[blockIdx.x * DH + tid];
    __syncthreads();
    float m = -INFINITY;
    for (int k = tid; k < WIN; k += 128) {
        float acc = 0.f;
        for (int d = 0; d < DH; d++) acc += q[d] * __bfloat162float(p.k[br][base + (size_t)k * DH + d]);
        acc = bf16r(bf16r(acc) * 0.08838834764831845f);
        s[k] = acc; m = fmaxf(m, acc);
    }
    red[tid] = m; __syncthreads();
    for (int i = 0; i < 128; i++) m = fmaxf(m, red[i]);
    __syncthreads();
    float sum = 0.f;
    for (int k = tid; k < WIN; k += 128) { float e = __expf(s[k] - m); s[k] = e; sum += e; }
    red[tid] = sum; __syncthreads();
    sum = 0.f;
    for (int i = 0; i < 128; i++) sum += red[i];
    const float inv = 1.0f / sum;
    float acc = 0.f;
    for (int k = 0; k < WIN; k++) acc += bf16r(s[k] * inv) * __bfloat162float(p.v[br][base + (size_t)k * DH + tid]);
    g_fb_o[blockIdx.x * DH + tid] = bf16r(acc);
}
__global__ void fb_oproj(Ptrs p, __nv_bfloat16* out) {
    const int idx = blockIdx.x * blockDim.x + threadIdx.x;
    if (idx >= NB * 2 * DM) return;
    const int b = idx / (2 * DM), c = idx % (2 * DM), br = c / DM, col = c % DM;
    float acc = 0.f;
    for (int k = 0; k < HQ * DH; k++) acc += g_fb_o[(br * NB + b) * HQ * DH + k] * __bfloat162float(p.wo[br][k * DM + col]);
    out[idx] = __float2bfloat16_rn(acc);
}

typedef CUresult (*EncodeFn)(CUtensorMap*, CUtensorMapDataType, cuuint32_t, void*, const cuuint64_t*, const cuuint64_t*,
                             const cuuint32_t*, const cuuint32_t*, CUtensorMapInterleave, CUtensorMapSwizzle,
                             CUtensorMapL2promotion, CUtensorMapFloatOOBfill);

bool encode_maps(Maps& m, void* const* d_in) {
    void* fn = nullptr;
    cudaDriverEntryPointQueryResult qr;
    if (cudaGetDriverEntryPoint("cuTensorMapEncodeTiled", &fn, cudaEnableDefault, &qr) != cudaSuccess || !fn) return false;
    EncodeFn enc = (EncodeFn)fn;
    const cuuint32_t es[3] = {1, 1, 1};
    bool ok = true;
    for (int br = 0; br < 2; br++) {
        {
            const cuuint64_t dims[2] = {64, (cuuint64_t)NB * HKV * SK * 2}, str[1] = {128};
            const cuuint32_t box[2] = {64, TILE_KEYS * 2 / SUB};
            ok &= enc(&m.k[br], CU_TENSOR_MAP_DATA_TYPE_BFLOAT16, 2, d_in[br * 5 + 1], dims, str, box, es, CU_TENSOR_MAP_INTERLEAVE_NONE,
                      CU_TENSOR_MAP_SWIZZLE_128B, CU_TENSOR_MAP_L2_PROMOTION_NONE, CU_TENSOR_MAP_FLOAT_OOB_FILL_NONE) == CUDA_SUCCESS;
            ok &= enc(&m.v[br], CU_TENSOR_MAP_DATA_TYPE_BFLOAT16, 2, d_in[br * 5 + 2], dims, str, box, es, CU_TENSOR_MAP_INTERLEAVE_NONE,
                      CU_TENSOR_MAP_SWIZZLE_128B, CU_TENSOR_MAP_L2_PROMOTION_NONE, CU_TENSOR_MAP_FLOAT_OOB_FILL_NONE) == CUDA_SUCCESS;
        }
        {
            const cuuint64_t dims[2] = {(cuuint64_t)HQ * DH, DM}, str[1] = {(cuuint64_t)HQ * DH * 2};
            const cuuint32_t box[2] = {64, DM / NWQ};
            ok &= enc(&m.wq[br], CU_TENSOR_MAP_DATA_TYPE_BFLOAT16, 2, d_in[br * 5 + 3], dims, str, box, es, CU_TENSOR_MAP_INTERLEAVE_NONE,
                      CU_TENSOR_MAP_SWIZZLE_128B, CU_TENSOR_MAP_L2_PROMOTION_NONE, CU_TENSOR_MAP_FLOAT_OOB_FILL_NONE) == CUDA_SUCCESS;
        }
        {
            const cuuint64_t dims[2] = {DM, (cuuint64_t)HQ * DH}, str[1] = {DM * 2};
            const cuuint32_t box[2] = {16, 256};
            ok &= enc(&m.wo[br], CU_TENSOR_MAP_DATA_TYPE_BFLOAT16, 2, d_in[br * 5 + 4], dims, str, box, es, CU_TENSOR_MAP_INTERLEAVE_NONE,
                      CU_TENSOR_MAP_SWIZZLE_32B, CU_TENSOR_MAP_L2_PROMOTION_L2_128B, CU_TENSOR_MAP_FLOAT_OOB_FILL_NONE) == CUDA_SUCCESS;
        }
    }
    return ok;
}

}

static int g_tau = (int)(1290.0 / 32768.0 * 1048576.0), g_delta = 1000, g_lead = 1800, g_taper = 900, g_ptaper = 9, g_ostep = WO_STEP;

extern "C" void kernel_launch(void* const* d_in, const int* in_sizes, int n_in, void* d_out, int out_size) {
    (void)in_sizes; (void)n_in; (void)out_size;
    static int fast_ok = -1;
    if (fast_ok < 0) {
        int dev = 0, sms = 0, nb = 0;
        bool ok = cudaGetDevice(&dev) == cudaSuccess &&
                  cudaDeviceGetAttribute(&sms, cudaDevAttrMultiProcessorCount, dev) == cudaSuccess &&
                  cudaFuncSetAttribute(fused_decode_kernel, cudaFuncAttributeMaxDynamicSharedMemorySize, SMEM_BYTES) == cudaSuccess &&
                  cudaOccupancyMaxActiveBlocksPerMultiprocessor(&nb, fused_decode_kernel, NTHREADS, SMEM_BYTES) == cudaSuccess &&
                  sms * nb >= NCTA;
        int khz = 0, bits = 0;
        if (cudaDeviceGetAttribute(&khz, cudaDevAttrMemoryClockRate, dev) == cudaSuccess &&
            cudaDeviceGetAttribute(&bits, cudaDevAttrGlobalMemoryBusWidth, dev) == cudaSuccess && khz > 0 && bits > 0)
            g_tau = (int)(g_tau * (2619000.0 * 5120.0) / ((double)khz * bits) + 0.5);
        fast_ok = ok ? 1 : 0;
        (void)cudaGetLastError();
    }
    Maps maps;
    if (fast_ok == 1 && encode_maps(maps, d_in)) {
        fused_decode_kernel<<<NCTA, NTHREADS, SMEM_BYTES>>>((const __nv_bfloat16*)d_in[0], (const __nv_bfloat16*)d_in[5],
                                                           (__nv_bfloat16*)d_out, g_tau, g_delta, g_lead, g_taper, g_ptaper, g_ostep, maps);
        return;
    }
    Ptrs p;
    for (int br = 0; br < 2; br++) {
        p.x[br] = (const __nv_bfloat16*)d_in[br * 5 + 0]; p.k[br] = (const __nv_bfloat16*)d_in[br * 5 + 1];
        p.v[br] = (const __nv_bfloat16*)d_in[br * 5 + 2]; p.wq[br] = (const __nv_bfloat16*)d_in[br * 5 + 3];
        p.wo[br] = (const __nv_bfloat16*)d_in[br * 5 + 4];
    }
    fb_qproj<<<2 * NB * HQ * DH / 256, 256>>>(p);
    fb_attn<<<2 * NB * HQ, 128>>>(p);
    fb_oproj<<<(NB * 2 * DM + 127) / 128, 128>>>(p, (__nv_bfloat16*)d_out);
}
```

```cpp
#include <cuda_runtime.h>
#include <cuda_bf16.h>
#include <cuda.h>
#include <stdint.h>

namespace {

constexpr int NB = 4, DM = 576, HQ = 32, HKV = 16, SK = 8192, DH = 128, WIN = 2048;
constexpr int NCTA = 128;
constexpr int NST = 4;
constexpr int SUB = 2;
constexpr int NWQ = 3;
constexpr int NPRE = 5;
constexpr int REP_FIRST = 5, REP_LAST = 29;
constexpr int TILE_KEYS = 128;
constexpr int STAGE_BYTES = TILE_KEYS * DH * 2;
constexpr int NTILE = WIN / TILE_KEYS;
constexpr int WBUF_BYTES = 73728;
constexpr int NOWN = DM / 16;
constexpr int NWO = HKV;
constexpr int WO_BOX_BYTES = 256 * 32;
constexpr int WO_STEP = WBUF_BYTES / NWO;
constexpr int XPITCH = 1168;

constexpr int OFF_STAGE = 0;
constexpr int OFF_WBUF = OFF_STAGE + NST * STAGE_BYTES;
constexpr int OFF_S = OFF_WBUF + WBUF_BYTES;
constexpr int OFF_WO = OFF_S - NWO * WO_BOX_BYTES;
constexpr int OFF_Q = OFF_S + 16384;
constexpr int OFF_ORED = OFF_Q + 512;
constexpr int OFF_RED = OFF_ORED + 2 * 288 * 4;
constexpr int OFF_CTL = OFF_RED + 128;
constexpr int OFF_BAR = OFF_CTL + 16;
constexpr int SMEM_BYTES = OFF_BAR + 448;
constexpr uint32_t SMEM_BASE = 1024;

constexpr int NTHREADS = 352;
constexpr unsigned SPIN_LIMIT = 1u << 24;
constexpr uint64_t EVICT_FIRST = 0x12F0000000000000ull;

struct Maps { CUtensorMap k[2], v[2], wq[2], wo[2]; };

__device__ __align__(128) unsigned long long g_qx[NCTA * 128];
__device__ __align__(128) uint32_t g_ox[NCTA * 128];
__device__ __align__(128) unsigned int g_ready[32];
__device__ __align__(128) unsigned int g_epoch[NCTA * 32];
__device__ __align__(128) unsigned long long g_prog[2 * NTILE * 16];

__device__ __forceinline__ uint32_t gtime32() { uint32_t t; asm volatile("mov.u32 %0, %%globaltimer_lo;" : "=r"(t)); return t; }

__device__ __forceinline__ uint32_t smem_u32(const void* p) { return (uint32_t)__cvta_generic_to_shared(p); }
__device__ __forceinline__ void mbar_init(uint32_t a, uint32_t c) { asm volatile("mbarrier.init.shared::cta.b64 [%0], %1;" :: "r"(a), "r"(c) : "memory"); }
__device__ __forceinline__ void mbar_expect_tx(uint32_t a, uint32_t b) { asm volatile("mbarrier.arrive.expect_tx.shared::cta.b64 _, [%0], %1;" :: "r"(a), "r"(b) : "memory"); }
__device__ __forceinline__ void mbar_arrive(uint32_t a) { asm volatile("mbarrier.arrive.shared::cta.b64 _, [%0];" :: "r"(a) : "memory"); }
__device__ __forceinline__ bool mbar_try(uint32_t a, uint32_t ph) {
    uint32_t ok;
    asm volatile("{\n.reg .pred p;\nmbarrier.try_wait.parity.shared::cta.b64 p, [%1], %2;\nselp.u32 %0, 1, 0, p;\n}"
                 : "=r"(ok) : "r"(a), "r"(ph) : "memory");
    return ok != 0;
}
__device__ __forceinline__ void mbar_wait(uint32_t a, uint32_t ph) {
    uint32_t ok; unsigned it = 0;
    do {
        asm volatile("{\n.reg .pred p;\nmbarrier.try_wait.parity.shared::cta.b64 p, [%1], %2;\nselp.u32 %0, 1, 0, p;\n}"
                     : "=r"(ok) : "r"(a), "r"(ph) : "memory");
        if (++it > SPIN_LIMIT) __trap();
    } while (!ok);
}
__device__ __forceinline__ bool mbar_test(uint32_t a, uint32_t ph) {
    uint32_t ok;
    asm volatile("{\n.reg .pred p;\nmbarrier.test_wait.parity.shared::cta.b64 p, [%1], %2;\nselp.u32 %0, 1, 0, p;\n}"
                 : "=r"(ok) : "r"(a), "r"(ph) : "memory");
    return ok != 0;
}
__device__ __forceinline__ void bulk_g2s(uint32_t dst, const void* src, uint32_t bytes, uint32_t bar) {
    asm volatile("cp.async.bulk.shared::cluster.global.mbarrier::complete_tx::bytes [%0], [%1], %2, [%3];"
                 :: "r"(dst), "l"(src), "r"(bytes), "r"(bar) : "memory");
}
__device__ __forceinline__ void tma2d(uint32_t dst, const CUtensorMap* m, int c0, int c1, uint32_t bar, uint64_t pol) {
    asm volatile("cp.async.bulk.tensor.2d.shared::cluster.global.mbarrier::complete_tx::bytes.L2::cache_hint [%0], [%1, {%3, %4}], [%2], %5;"
                 :: "r"(dst), "l"(m), "r"(bar), "r"(c0), "r"(c1), "l"(pol) : "memory");
}
__device__ __forceinline__ void tma2d_nohint(uint32_t dst, const CUtensorMap* m, int c0, int c1, uint32_t bar) {
    asm volatile("cp.async.bulk.tensor.2d.shared::cluster.global.mbarrier::complete_tx::bytes [%0], [%1, {%3, %4}], [%2];"
                 :: "r"(dst), "l"(m), "r"(bar), "r"(c0), "r"(c1) : "memory");
}
__device__ __forceinline__ void ldsm4(uint32_t (&r)[4], uint32_t a) {
    asm volatile("ldmatrix.sync.aligned.m8n8.x4.shared.b16 {%0,%1,%2,%3}, [%4];"
                 : "=r"(r[0]), "=r"(r[1]), "=r"(r[2]), "=r"(r[3]) : "r"(a));
}
__device__ __forceinline__ void ldsm4t(uint32_t (&r)[4], uint32_t a) {
    asm volatile("ldmatrix.sync.aligned.m8n8.x4.trans.shared.b16 {%0,%1,%2,%3}, [%4];"
                 : "=r"(r[0]), "=r"(r[1]), "=r"(r[2]), "=r"(r[3]) : "r"(a));
}
__device__ __forceinline__ void mma16816(float (&c)[4], const uint32_t (&a)[4], uint32_t b0, uint32_t b1) {
    asm("mma.sync.aligned.m16n8k16.row.col.f32.bf16.bf16.f32 {%0,%1,%2,%3}, {%4,%5,%6,%7}, {%8,%9}, {%0,%1,%2,%3};"
                 : "+f"(c[0]), "+f"(c[1]), "+f"(c[2]), "+f"(c[3])
                 : "r"(a[0]), "r"(a[1]), "r"(a[2]), "r"(a[3]), "r"(b0), "r"(b1));
}
__device__ __forceinline__ uint32_t lds32(uint32_t a) { uint32_t v; asm volatile("ld.shared.u32 %0, [%1];" : "=r"(v) : "r"(a)); return v; }
__device__ __forceinline__ void sts32(uint32_t a, float v) { asm volatile("st.shared.f32 [%0], %1;" :: "r"(a), "f"(v) : "memory"); }
__device__ __forceinline__ float4 lds128f(uint32_t a) {
    float4 v; asm volatile("ld.shared.v4.f32 {%0,%1,%2,%3}, [%4];" : "=f"(v.x), "=f"(v.y), "=f"(v.z), "=f"(v.w) : "r"(a) : "memory"); return v;
}
__device__ __forceinline__ void bar_sync(int id, int n) { asm volatile("bar.sync %0, %1;" :: "r"(id), "r"(n) : "memory"); }

__device__ __forceinline__ void st_word(uint32_t* p, uint32_t w) { asm volatile("st.relaxed.gpu.global.u32 [%0], %1;" :: "l"(p), "r"(w) : "memory"); }
__device__ __forceinline__ void st_u64(unsigned long long* p, unsigned long long w) { asm volatile("st.relaxed.gpu.global.u64 [%0], %1;" :: "l"(p), "l"(w) : "memory"); }
__device__ __forceinline__ void st_zero4(uint32_t* p) { asm volatile("st.relaxed.gpu.global.v4.u32 [%0], {%1, %1, %1, %1};" :: "l"(p), "r"(0u) : "memory"); }
__device__ __forceinline__ uint4 ld_word4(const uint32_t* p) {
    uint4 v;
    asm volatile("ld.relaxed.gpu.global.v4.u32 {%0, %1, %2, %3}, [%4];" : "=r"(v.x), "=r"(v.y), "=r"(v.z), "=r"(v.w) : "l"(p) : "memory");
    return v;
}
__device__ __forceinline__ bool all_set(const uint4& v) { return min(min(v.x, v.y), min(v.z, v.w)) != 0u; }
__device__ __forceinline__ unsigned long long ld_u64(const unsigned long long* p) {
    unsigned long long w;
    asm volatile("ld.relaxed.gpu.global.u64 %0, [%1];" : "=l"(w) : "l"(p) : "memory");
    return w;
}
__device__ __forceinline__ void ld_u64x2(const unsigned long long* p, unsigned long long& w0, unsigned long long& w1) {
    asm volatile("ld.relaxed.gpu.global.v2.u64 {%0, %1}, [%2];" : "=l"(w0), "=l"(w1) : "l"(p) : "memory");
}
__device__ __forceinline__ void st_zero2(unsigned long long* p) { asm volatile("st.relaxed.gpu.global.v2.u64 [%0], {%1, %1};" :: "l"(p), "l"(0ull) : "memory"); }
__device__ __forceinline__ int tile_slot(int i) { return i < NST + 2 ? i : ((i - NST - 2) & (NST - 1)); }
__device__ __forceinline__ uint32_t tile_par(int i) { return i < NST + 2 ? 0u : (uint32_t)((1 + ((i - NST - 2) >> 2)) & 1); }
__device__ __forceinline__ int cum_bytes(int i) { return WBUF_BYTES + i * STAGE_BYTES; }
__device__ __forceinline__ void pace(uint32_t t_start, int bytes, int tau, const volatile int* offset) {
    const int due = (int)(((long long)bytes * tau) >> 20);
    while ((int)(gtime32() - t_start) < due + *offset) {}
}
__device__ __forceinline__ float bf16r(float v) { return __bfloat162float(__float2bfloat16_rn(v)); }
__device__ __forceinline__ uint32_t pack_bf16(float lo, float hi) {
    __nv_bfloat162 t = __floats2bfloat162_rn(lo, hi);
    return *reinterpret_cast<uint32_t*>(&t);
}

__global__ void __launch_bounds__(NTHREADS, 1)
fused_decode_kernel(const __nv_bfloat16* __restrict__ xA, const __nv_bfloat16* __restrict__ xB, __nv_bfloat16* __restrict__ out,
                    int tau, int delta, int lead, int taper, int ow, int ostep,
                    const __grid_constant__ Maps maps) {
    extern __shared__ __align__(1024) unsigned char sp[];
    constexpr uint32_t sb = SMEM_BASE;

    const int tid = threadIdx.x, cta = blockIdx.x, br = cta >> 6;
    constexpr uint32_t bar_full = sb + OFF_BAR, bar_empty = bar_full + 8 * (NST + 2);
    constexpr uint32_t bar_wq = bar_empty + 8 * NST, bar_wqfree = bar_wq + 8 * (NWQ + 1), bar_go = bar_wqfree + 8, bar_q = bar_go + 8,
                       bar_rdy = bar_q + 8, bar_chk = bar_rdy + 8, bar_wo = bar_chk + 8;
    {
        uint64_t wqmap;
        asm volatile("mov.b64 %0, %1;" : "=l"(wqmap) : "l"(&maps.wq[0]));
        const int first = tid | (((uint32_t)wqmap & 63u) << 10);
#pragma unroll
        for (int w = 0; w < NWQ; w++)
            if (first == 32 * w) {
                mbar_init(bar_wq + 8 * w, 1);
                asm volatile("fence.mbarrier_init.release.cluster;" ::: "memory");
                tma2d(sb + OFF_WBUF + w * (DM / NWQ) * 128, (const CUtensorMap*)wqmap + br, (cta & 63) * 64, w * (DM / NWQ), bar_wq + 8 * w, EVICT_FIRST);
                mbar_expect_tx(bar_wq + 8 * w, WBUF_BYTES / NWQ);
            }
        if (tid == 32 * NWQ) {
            mbar_init(bar_wq + 8 * NWQ, 1);
            asm volatile("fence.mbarrier_init.release.cluster;" ::: "memory");
            mbar_expect_tx(bar_wq + 8 * NWQ, NB * DM * 2);
            const __nv_bfloat16* x = br ? xB : xA;
#pragma unroll
            for (int b = 0; b < NB; b++) bulk_g2s(sb + OFF_S + b * XPITCH, x + b * DM, DM * 2, bar_wq + 8 * NWQ);
        }
    }
    const int warp = tid >> 5, lane = tid & 31;
    const int g = lane >> 2, t = lane & 3;
    const int hkv = (cta >> 2) & 15, r = cta & 3;
    const int strip = !(cta & 1) ? (cta & 63) >> 1 : (cta & 15) == 1 ? 32 + ((cta & 63) >> 4) : NOWN;
    const int row0 = ((r * HKV + hkv) * SK + (SK - WIN)) * 2;

    uint32_t t_start = 0;
    volatile int* ctl = reinterpret_cast<volatile int*>(sp + OFF_CTL);
    if (tid == 256) {
        t_start = gtime32();
        for (int i = 0; i < NST + 2; i++) mbar_init(bar_full + 8 * i, 1);
        for (int i = 0; i < NST; i++) mbar_init(bar_empty + 8 * i, 8);
        ctl[0] = -delta; ctl[1] = (int)t_start;
        mbar_init(bar_wqfree, 4);
        mbar_init(bar_go, 1);
        mbar_init(bar_q, 1);
        mbar_init(bar_rdy, 2);
        mbar_init(bar_chk, 1);
        for (int i = 0; i < NWO; i++) mbar_init(bar_wo + 8 * i, 1);
        asm volatile("fence.mbarrier_init.release.cluster;" ::: "memory");
        for (int i = 0; i < NWO; i++) mbar_expect_tx(bar_wo + 8 * i, WO_BOX_BYTES);
    }
    uint32_t epoch;
    asm volatile("ld.relaxed.gpu.global.u32 %0, [%1];" : "=r"(epoch) : "l"(&g_epoch[cta * 32 + lane]) : "memory");
    if (warp == 10) st_zero4(&g_ox[cta * 128 + lane * 4]);
    if (warp == 4 || warp == 5) st_zero2(&g_qx[((cta & ~3) + ((tid - 128) >> 4)) * 128 + r * 32 + (lane & 15) * 2]);
    if (warp == 6 && cta < 2 * NTILE && lane < 8) st_zero2(&g_prog[cta * 16 + lane * 2]);
    __syncthreads();

    if (warp == 9) {
        mbar_wait(bar_wqfree, 0);
        epoch += 1u;
        const unsigned long long* qsrc = &g_qx[cta * 128 + lane * 4];
        unsigned long long u0, u1, u2, u3;
        for (unsigned it = 0;; it++) {
            ld_u64x2(qsrc, u0, u1); ld_u64x2(qsrc + 2, u2, u3);
            if ((uint32_t)(u0 >> 32) == epoch && (uint32_t)(u1 >> 32) == epoch && (uint32_t)(u2 >> 32) == epoch && (uint32_t)(u3 >> 32) == epoch) break;
            if (it > SPIN_LIMIT) __trap();
            __nanosleep(100);
        }
        const uint4 w = make_uint4((uint32_t)u0, (uint32_t)u1, (uint32_t)u2, (uint32_t)u3);
        uint2* qs = reinterpret_cast<uint2*>(sp + OFF_Q + (lane >> 1) * 32 + (lane & 1) * 8);
        qs[0] = make_uint2(__byte_perm(w.x, w.y, 0x5410), __byte_perm(w.z, w.w, 0x5410));
        qs[2] = make_uint2(__byte_perm(w.x, w.y, 0x7632), __byte_perm(w.z, w.w, 0x7632));
        __syncwarp();
        if (lane == 0) {
            mbar_arrive(bar_q);
            for (unsigned it = 0;; it++) {
                unsigned v;
                asm volatile("ld.acquire.gpu.global.u32 %0, [%1];" : "=r"(v) : "l"(g_ready) : "memory");
                if ((int)(v - epoch * NCTA) >= 0) break;
                if (it > SPIN_LIMIT) __trap();
                __nanosleep(200);
            }
            mbar_arrive(bar_rdy);
            mbar_arrive(bar_chk);
            unsigned long long* prog = g_prog;
            const uint32_t t0 = (uint32_t)ctl[1];
            for (int i = REP_FIRST; i <= REP_LAST; i++) {
                while (!mbar_try(bar_full + 8 * tile_slot(i), tile_par(i)))
                    if (mbar_test(bar_go, 0)) return;
                const unsigned long long v = (1ull << 40) | (unsigned long long)min(gtime32() - t0, 1u << 24);
                asm volatile("red.relaxed.gpu.global.add.u64 [%0], %1;" :: "l"(prog + i * 16), "l"(v) : "memory");
            }
        }
        return;
    }
    if (warp == 10) {
        if (lane == 0) asm volatile("red.release.gpu.global.add.u32 [%0], %1;" :: "l"(g_ready), "r"(1u) : "memory");
        if (smem_u32(sp) != sb) __trap();
        mbar_wait(bar_q, 0);
        epoch += 1u;
        g_epoch[cta * 32 + lane] = epoch;
        if (lane == 0) {
            const unsigned long long* prog = g_prog;
            mbar_wait(bar_full + 8 * tile_slot(REP_FIRST - 1), tile_par(REP_FIRST - 1));
            mbar_wait(bar_chk, 0);
            int n = REP_FIRST;
            for (unsigned it = 0; n <= REP_LAST && it < SPIN_LIMIT && !mbar_test(bar_go, 0); it++) {
                unsigned long long w = ld_u64(prog + n * 16);
                const unsigned long long w1 = ld_u64(prog + (n + 1) * 16);
                if ((w1 >> 40) == NCTA) { w = w1; n++; }
                if ((w >> 40) == NCTA) {
                    const int avg = (int)((w & ((1ull << 40) - 1)) / NCTA);
                    const int off = avg - (int)(((long long)cum_bytes(n + 1) * tau) >> 20) - lead;
                    ctl[0] = max(-delta - 4000, min(off, 8000));
                    n++;
                } else {
                    __nanosleep(200);
                }
            }
        }
        return;
    }
    if (warp == 8) {
        if (lane == 0) {
            for (int i = 0; i < 2 * NTILE; i++) {
                const int slot = tile_slot(i);
                if (i >= NST + 2) mbar_wait(bar_empty + 8 * slot, tile_par(i) ^ 1);
                else if (i == NST) mbar_wait(bar_wqfree, 0);
                const CUtensorMap* m = (i < NTILE) ? &maps.k[br] : &maps.v[br];
#pragma unroll
                for (int sub = 0; sub < SUB; sub++) {
                    pace(t_start, cum_bytes(i) + sub * (STAGE_BYTES / SUB), tau, ctl);
                    if (sub == 0) mbar_expect_tx(bar_full + 8 * slot, STAGE_BYTES);
                    tma2d(sb + OFF_STAGE + slot * STAGE_BYTES + sub * (STAGE_BYTES / SUB), m, 0,
                          row0 + (i & (NTILE - 1)) * TILE_KEYS * 2 + sub * (TILE_KEYS * 2 / SUB), bar_full + 8 * slot, EVICT_FIRST);
                }
            }
            mbar_arrive(bar_go);
            if (strip < NOWN) {
                mbar_wait(bar_empty + 8 * tile_slot(2 * NTILE), tile_par(2 * NTILE) ^ 1);
                mbar_wait(bar_empty + 8 * tile_slot(2 * NTILE + 1), tile_par(2 * NTILE + 1) ^ 1);
                uint32_t due = t_start + taper + ctl[0] + (int)(((long long)cum_bytes(2 * NTILE) * tau) >> 20);
                const uint32_t step = (uint32_t)(((long long)ostep * tau) >> 20);
                const CUtensorMap* m = &maps.wo[br];
#pragma unroll 1
                for (int i = 0; i < NWO; i++, due += step) {
                    while ((int)(gtime32() - due) < 0) {}
                    tma2d_nohint(sb + OFF_WO + i * WO_BOX_BYTES, m, strip * 16, i * 256, bar_wo + 8 * i);
                    if (i == ow) mbar_arrive(bar_rdy);
                }
            }
        }
        return;
    }
    {
        if (warp < 4) {
            for (int j = NWQ; j >= 0; j--) mbar_wait(bar_wq + 8 * j, 0);
            float c0[4] = {0.f, 0.f, 0.f, 0.f}, c1[4] = {0.f, 0.f, 0.f, 0.f};
            const int mi = lane >> 3, i8 = lane & 7;
            const uint32_t abase = sb + OFF_WBUF + (i8 + 8 * (mi >> 1)) * 128 + (((2 * warp + (mi & 1)) ^ i8) << 4);
            const uint32_t xb = sb + OFF_S + (g & 3) * XPITCH + t * 4;
#pragma unroll 6
            for (int ks = 0; ks < 36; ks += 2) {
                uint32_t a[4], a2[4];
                ldsm4t(a, abase + ks * 2048);
                ldsm4t(a2, abase + ks * 2048 + 2048);
                uint32_t b0 = lds32(xb + ks * 32), b1 = lds32(xb + ks * 32 + 16);
                uint32_t b2 = lds32(xb + ks * 32 + 32), b3 = lds32(xb + ks * 32 + 48);
                mma16816(c0, a, b0, b1);
                mma16816(c1, a2, b2, b3);
            }
            __syncwarp();
            if (lane == 0) mbar_arrive(bar_wqfree);
            epoch += 1u;
            if (t < 2) {
#pragma unroll
                for (int e = 0; e < 2; e++)
                    st_u64(&g_qx[((cta & ~3) + 2 * t + e) * 128 + r * 32 + warp * 8 + g],
                           ((unsigned long long)epoch << 32) | pack_bf16(c0[e] + c1[e], c0[2 + e] + c1[2 + e]));
            }
        }
        mbar_wait(bar_q, 0);

        {
            uint32_t qb[2][4][2];
            const int h = g & 1, sel = (g >> 1) & 1;
#pragma unroll
            for (int p = 0; p < 2; p++)
#pragma unroll
                for (int s = 0; s < 4; s++) {
                    const uint32_t a = sb + OFF_Q + (h * 128 + ((sel ^ p) * 64) + s * 16 + 2 * t) * 2;
                    qb[p][s][0] = lds32(a);
                    qb[p][s][1] = lds32(a + 16);
                }
            const int mi = lane >> 3, i8 = lane & 7;
            const int key = warp * 16 + i8 + 8 * (mi & 1);
            uint32_t koff[2];
#pragma unroll
            for (int p = 0; p < 2; p++) {
                const int j = 2 * key + ((i8 >> 2) ^ p);
                koff[p] = j * 128 + (((mi >> 1) ^ (j & 7)) << 4);
            }
            float2* S = reinterpret_cast<float2*>(sp + OFF_S);
            const bool valid = (t == (g >> 2));
            const float scale = 0.08838834764831845f;
#pragma unroll 1
            for (int it = 0; it < NTILE; it++) {
                const int st = tile_slot(it);
                mbar_wait(bar_full + 8 * st, tile_par(it));
                const uint32_t base = sb + OFF_STAGE + st * STAGE_BYTES;
                float ca[4] = {0.f, 0.f, 0.f, 0.f}, cb[4] = {0.f, 0.f, 0.f, 0.f};
#pragma unroll
                for (int s = 0; s < 4; s++) {
                    uint32_t a[4], a2[4];
                    ldsm4(a, base + (koff[0] ^ (s << 5)));
                    ldsm4(a2, base + (koff[1] ^ (s << 5)));
                    mma16816(ca, a, qb[0][s][0], qb[0][s][1]);
                    mma16816(cb, a2, qb[1][s][0], qb[1][s][1]);
                }
                __syncwarp();
                if (lane == 0 && st < NST) mbar_arrive(bar_empty + 8 * st);
                const float2 s0 = make_float2(bf16r(bf16r(ca[0] + cb[0]) * scale), bf16r(bf16r(ca[1] + cb[1]) * scale));
                const float2 s1 = make_float2(bf16r(bf16r(ca[2] + cb[2]) * scale), bf16r(bf16r(ca[3] + cb[3]) * scale));
                if (valid) {
                    const int k0 = it * TILE_KEYS + warp * 16 + g;
                    S[k0] = s0;
                    S[k0 + 8] = s1;
                }
            }
            bar_sync(1, 256);
        }

        {
            const int gp = tid >> 2, tt = tid & 3;
            float4 sv[4];
#pragma unroll
            for (int j = 0; j < 4; j++)
                sv[j] = *reinterpret_cast<const float4*>(sp + OFF_S + (gp * 32 + j * 8 + 2 * tt) * 8);
            float m0 = -INFINITY, m1 = -INFINITY;
#pragma unroll
            for (int j = 0; j < 4; j++) {
                m0 = fmaxf(m0, fmaxf(sv[j].x, sv[j].z));
                m1 = fmaxf(m1, fmaxf(sv[j].y, sv[j].w));
            }
#pragma unroll
            for (int o = 16; o; o >>= 1) {
                m0 = fmaxf(m0, __shfl_xor_sync(0xffffffffu, m0, o));
                m1 = fmaxf(m1, __shfl_xor_sync(0xffffffffu, m1, o));
            }
            float2* red = reinterpret_cast<float2*>(sp + OFF_RED);
            if (lane == 0) red[warp] = make_float2(m0, m1);
            bar_sync(1, 256);
#pragma unroll
            for (int w = 0; w < 8; w++) { float2 v = red[w]; m0 = fmaxf(m0, v.x); m1 = fmaxf(m1, v.y); }
            float s0 = 0.f, s1 = 0.f;
#pragma unroll
            for (int j = 0; j < 4; j++) {
                sv[j].x = __expf(sv[j].x - m0); sv[j].z = __expf(sv[j].z - m0);
                sv[j].y = __expf(sv[j].y - m1); sv[j].w = __expf(sv[j].w - m1);
                s0 += sv[j].x + sv[j].z; s1 += sv[j].y + sv[j].w;
            }
#pragma unroll
            for (int o = 16; o; o >>= 1) {
                s0 += __shfl_xor_sync(0xffffffffu, s0, o);
                s1 += __shfl_xor_sync(0xffffffffu, s1, o);
            }
            if (lane == 0) red[8 + warp] = make_float2(s0, s1);
            bar_sync(1, 256);
            s0 = 0.f; s1 = 0.f;
#pragma unroll
            for (int w = 0; w < 8; w++) { float2 v = red[8 + w]; s0 += v.x; s1 += v.y; }
            const float i0 = 1.0f / s0, i1 = 1.0f / s1;
            uint4 p0, p1;
            p0.x = pack_bf16(sv[0].x * i0, sv[0].z * i0); p1.x = pack_bf16(sv[0].y * i1, sv[0].w * i1);
            p0.y = pack_bf16(sv[1].x * i0, sv[1].z * i0); p1.y = pack_bf16(sv[1].y * i1, sv[1].w * i1);
            p0.z = pack_bf16(sv[2].x * i0, sv[2].z * i0); p1.z = pack_bf16(sv[2].y * i1, sv[2].w * i1);
            p0.w = pack_bf16(sv[3].x * i0, sv[3].z * i0); p1.w = pack_bf16(sv[3].y * i1, sv[3].w * i1);
            *reinterpret_cast<uint4*>(sp + OFF_S + gp * 128 + tt * 16) = p0;
            *reinterpret_cast<uint4*>(sp + OFF_S + gp * 128 + 64 + tt * 16) = p1;
            bar_sync(1, 256);
        }

        {
            float oa[4] = {0.f, 0.f, 0.f, 0.f}, ob[4] = {0.f, 0.f, 0.f, 0.f};
            const int mt = warp & 3, p = warp >> 2;
            const int mi = lane >> 3, i8 = lane & 7;
            const int j = 2 * (i8 + 8 * (mi >> 1)) + ((i8 >> 2) ^ p);
            const uint32_t voff = j * 128 + (((2 * mt + (mi & 1)) ^ (j & 7)) << 4);
            const bool live = (g < 4) && (((g >> 1) & 1) == ((t >> 1) ^ p));
            const unsigned char* pp = sp + OFF_S + (g & 1) * 64 + t * 16;
#pragma unroll 1
            for (int it = 0; it < NTILE; it++) {
                uint4 pf[4];
#pragma unroll
                for (int q = 0; q < 4; q++) {
                    pf[q] = *reinterpret_cast<const uint4*>(pp + (it * 4 + q) * 128);
                    if (!live) pf[q] = make_uint4(0u, 0u, 0u, 0u);
                }
                const int st = tile_slot(NTILE + it);
                mbar_wait(bar_full + 8 * st, tile_par(NTILE + it));
                const uint32_t base = sb + OFF_STAGE + st * STAGE_BYTES + voff;
#pragma unroll
                for (int q = 0; q < 4; q++) {
                    uint32_t a[4], a2[4];
                    ldsm4t(a, base + q * 8192);
                    ldsm4t(a2, base + q * 8192 + 4096);
                    mma16816(oa, a, pf[q].x, pf[q].y);
                    mma16816(ob, a2, pf[q].z, pf[q].w);
                }
                __syncwarp();
                if (lane == 0) mbar_arrive(bar_empty + 8 * st);
            }
            float* ored = reinterpret_cast<float*>(sp + OFF_ORED);
            if (t < 2) {
                float* d = ored + p * 288 + 72 * t + 16 * mt + g;
                d[0] = oa[0] + ob[0]; d[144] = oa[1] + ob[1]; d[8] = oa[2] + ob[2]; d[152] = oa[3] + ob[3];
            }
            bar_sync(1, 256);
            if (warp < 4) {
                const float* s = ored + 72 * warp + 32 * (lane >> 4) + 8 * (lane & 3) + 2 * ((lane >> 2) & 3);
                const float2 u = *reinterpret_cast<const float2*>(s), v = *reinterpret_cast<const float2*>(s + 288);
                const uint32_t w = pack_bf16(u.x + v.x, u.y + v.y);
                st_word(&g_ox[cta * 128 + tid], w ? w : 0x8000u);
            }
        }
    }
    if (strip >= NOWN) return;

    {
        const int mi = lane >> 3, i8 = lane & 7, kg = warp & 3, bp = warp >> 2;
        const uint32_t abase = sb + OFF_WO + (64 * kg + i8 + 8 * (mi >> 1)) * 32 + (((mi & 1) ^ (i8 >> 2)) << 4);
        const uint32_t* osrc = &g_ox[(br * 64 + bp * 4 + (g & 3)) * 128 + kg * 32 + (g >> 2) * 16 + t * 4];
        uint32_t abox = abase + bp * WO_BOX_BYTES, bbox = bar_wo + 8 * bp;
        __nv_bfloat16* dst = out + ((tid >> 4) & 3) * (2 * DM) + br * DM + strip * 16 + (tid & 15);
        uint32_t wr = sb + OFF_S + (((t & 1) * 32 + g) * 20 + ((2 * warp + (t >> 1)) ^ (2 * (t & 1)))) * 4;
        uint32_t rd = tid < 64 ? sb + OFF_S + tid * 80 : 0u, hf = t >> 1;
        asm volatile("" : "+l"(osrc), "+r"(abox), "+r"(bbox), "+l"(dst), "+r"(wr), "+r"(rd), "+r"(hf));
        float c[4][4];
#pragma unroll
        for (int i = 0; i < 16; i++) (&c[0][0])[i] = 0.f;
        auto box_mma = [&](int q, const uint4& b) {
            uint32_t a[4][4];
#pragma unroll
            for (int s = 0; s < 4; s++) ldsm4t(a[s], abox + q * 2 * WO_BOX_BYTES + s * 512);
            mma16816(c[0], a[0], b.x, b.y);
            mma16816(c[1], a[1], b.z, b.w);
            mma16816(c[2], a[2], b.x, b.y);
            mma16816(c[3], a[3], b.z, b.w);
        };
        uint4 of[8], nx[8];
        mbar_wait(bar_rdy, 0);
#pragma unroll
        for (int q = 0; q < 8; q++) of[q] = ld_word4(osrc + q * 8 * 128);
        uint32_t af[NPRE][4][4];
#pragma unroll
        for (int q = 0; q < NPRE; q++) {
            mbar_wait(bbox + 16 * q, 0);
#pragma unroll
            for (int s = 0; s < 4; s++) ldsm4t(af[q][s], abox + q * 2 * WO_BOX_BYTES + s * 512);
        }
        uint32_t miss = 0;
#pragma unroll
        for (int q = 0; q < NPRE; q++) {
            mma16816(c[0], af[q][0], of[q].x, of[q].y);
            mma16816(c[1], af[q][1], of[q].z, of[q].w);
            mma16816(c[2], af[q][2], of[q].x, of[q].y);
            mma16816(c[3], af[q][3], of[q].z, of[q].w);
        }
#pragma unroll
        for (int q = 0; q < 8; q++) {
            const bool m = !all_set(of[q]);
            if (m) nx[q] = ld_word4(osrc + q * 8 * 128);
            miss |= (uint32_t)m << q;
        }
        miss = __reduce_or_sync(0xffffffffu, miss);
#pragma unroll
        for (int q = NPRE; q < 7; q++) {
            mbar_wait(bbox + 16 * q, 0);
            box_mma(q, of[q]);
        }
        for (unsigned it = 0;; it++) {
            if (miss) {
                uint32_t still = 0;
#pragma unroll
                for (int q = 0; q < 8; q++)
                    if (miss >> q & 1) {
                        uint4 d;
                        d.x = of[q].x ? 0u : nx[q].x; d.y = of[q].y ? 0u : nx[q].y; d.z = of[q].z ? 0u : nx[q].z; d.w = of[q].w ? 0u : nx[q].w;
                        of[q].x |= d.x; of[q].y |= d.y; of[q].z |= d.z; of[q].w |= d.w;
                        const bool m = !all_set(of[q]);
                        if (m) nx[q] = ld_word4(osrc + q * 8 * 128);
                        still |= (uint32_t)m << q;
                        __syncwarp();
                        if (q < 7 || it) box_mma(q, d);
                    }
                miss = __reduce_or_sync(0xffffffffu, still);
            }
            if (it == 0) {
#pragma unroll
                for (int q = 7; q < 8; q++) {
                    mbar_wait(bbox + 16 * q, 0);
                    box_mma(q, of[q]);
                }
            }
            if (!miss) break;
            if (it > SPIN_LIMIT) __trap();
        }
        sts32(wr, hf ? c[2][0] + c[3][0] : c[0][0] + c[1][0]);
        sts32(wr + 16 * 80, hf ? c[2][1] + c[3][1] : c[0][1] + c[1][1]);
        sts32(wr + 8 * 80, hf ? c[2][2] + c[3][2] : c[0][2] + c[1][2]);
        sts32(wr + 24 * 80, hf ? c[2][3] + c[3][3] : c[0][3] + c[1][3]);
        bar_sync(1, 256);
        if (rd) {
            const float4 v0 = lds128f(rd), v1 = lds128f(rd + 16), v2 = lds128f(rd + 32), v3 = lds128f(rd + 48);
            const float acc = (((v0.x + v0.y) + (v0.z + v0.w)) + ((v1.x + v1.y) + (v1.z + v1.w))) +
                              (((v2.x + v2.y) + (v2.z + v2.w)) + ((v3.x + v3.y) + (v3.z + v3.w)));
            asm volatile("st.global.u16 [%0], %1;" :: "l"(dst), "h"(__bfloat16_as_ushort(__float2bfloat16_rn(acc))) : "memory");
        }
    }
}

__device__ float g_fb_q[2 * NB * HQ * DH];
__device__ float g_fb_o[2 * NB * HQ * DH];

struct Ptrs { const __nv_bfloat16 *x[2], *k[2], *v[2], *wq[2], *wo[2]; };

__global__ void fb_qproj(Ptrs p) {
    const int idx = blockIdx.x * blockDim.x + threadIdx.x;
    const int br = idx >> 14, b = (idx >> 12) & 3, col = idx & 4095;
    float acc = 0.f;
    for (int k = 0; k < DM; k++) acc += __bfloat162float(p.x[br][b * DM + k]) * __bfloat162float(p.wq[br][k * 4096 + col]);
    g_fb_q[idx] = bf16r(acc);
}
__global__ void fb_attn(Ptrs p) {
    __shared__ float s[WIN]; __shared__ float q[DH]; __shared__ float red[128];
    const int br = blockIdx.x >> 7, b = (blockIdx.x >> 5) & 3, h = blockIdx.x & 31, tid = threadIdx.x;
    const size_t base = ((size_t)(b * HKV + (h >> 1)) * SK + (SK - WIN)) * DH;
    q[tid] = g_fb_q[blockIdx.x * DH + tid];
    __syncthreads();
    float m = -INFINITY;
    for (int k = tid; k < WIN; k += 128) {
        float acc = 0.f;
        for (int d = 0; d < DH; d++) acc += q[d] * __bfloat162float(p.k[br][base + (size_t)k * DH + d]);
        acc = bf16r(bf16r(acc) * 0.08838834764831845f);
        s[k] = acc; m = fmaxf(m, acc);
    }
    red[tid] = m; __syncthreads();
    for (int i = 0; i < 128; i++) m = fmaxf(m, red[i]);
    __syncthreads();
    float sum = 0.f;
    for (int k = tid; k < WIN; k += 128) { float e = __expf(s[k] - m); s[k] = e; sum += e; }
    red[tid] = sum; __syncthreads();
    sum = 0.f;
    for (int i = 0; i < 128; i++) sum += red[i];
    const float inv = 1.0f / sum;
    float acc = 0.f;
    for (int k = 0; k < WIN; k++) acc += bf16r(s[k] * inv) * __bfloat162float(p.v[br][base + (size_t)k * DH + tid]);
    g_fb_o[blockIdx.x * DH + tid] = bf16r(acc);
}
__global__ void fb_oproj(Ptrs p, __nv_bfloat16* out) {
    const int idx = blockIdx.x * blockDim.x + threadIdx.x;
    if (idx >= NB * 2 * DM) return;
    const int b = idx / (2 * DM), c = idx % (2 * DM), br = c / DM, col = c % DM;
    float acc = 0.f;
    for (int k = 0; k < HQ * DH; k++) acc += g_fb_o[(br * NB + b) * HQ * DH + k] * __bfloat162float(p.wo[br][k * DM + col]);
    out[idx] = __float2bfloat16_rn(acc);
}

typedef CUresult (*EncodeFn)(CUtensorMap*, CUtensorMapDataType, cuuint32_t, void*, const cuuint64_t*, const cuuint64_t*,
                             const cuuint32_t*, const cuuint32_t*, CUtensorMapInterleave, CUtensorMapSwizzle,
                             CUtensorMapL2promotion, CUtensorMapFloatOOBfill);

bool encode_maps(Maps& m, void* const* d_in) {
    void* fn = nullptr;
    cudaDriverEntryPointQueryResult qr;
    if (cudaGetDriverEntryPoint("cuTensorMapEncodeTiled", &fn, cudaEnableDefault, &qr) != cudaSuccess || !fn) return false;
    EncodeFn enc = (EncodeFn)fn;
    const cuuint32_t es[3] = {1, 1, 1};
    bool ok = true;
    for (int br = 0; br < 2; br++) {
        {
            const cuuint64_t dims[2] = {64, (cuuint64_t)NB * HKV * SK * 2}, str[1] = {128};
            const cuuint32_t box[2] = {64, TILE_KEYS * 2 / SUB};
            ok &= enc(&m.k[br], CU_TENSOR_MAP_DATA_TYPE_BFLOAT16, 2, d_in[br * 5 + 1], dims, str, box, es, CU_TENSOR_MAP_INTERLEAVE_NONE,
                      CU_TENSOR_MAP_SWIZZLE_128B, CU_TENSOR_MAP_L2_PROMOTION_NONE, CU_TENSOR_MAP_FLOAT_OOB_FILL_NONE) == CUDA_SUCCESS;
            ok &= enc(&m.v[br], CU_TENSOR_MAP_DATA_TYPE_BFLOAT16, 2, d_in[br * 5 + 2], dims, str, box, es, CU_TENSOR_MAP_INTERLEAVE_NONE,
                      CU_TENSOR_MAP_SWIZZLE_128B, CU_TENSOR_MAP_L2_PROMOTION_NONE, CU_TENSOR_MAP_FLOAT_OOB_FILL_NONE) == CUDA_SUCCESS;
        }
        {
            const cuuint64_t dims[2] = {(cuuint64_t)HQ * DH, DM}, str[1] = {(cuuint64_t)HQ * DH * 2};
            const cuuint32_t box[2] = {64, DM / NWQ};
            ok &= enc(&m.wq[br], CU_TENSOR_MAP_DATA_TYPE_BFLOAT16, 2, d_in[br * 5 + 3], dims, str, box, es, CU_TENSOR_MAP_INTERLEAVE_NONE,
                      CU_TENSOR_MAP_SWIZZLE_128B, CU_TENSOR_MAP_L2_PROMOTION_NONE, CU_TENSOR_MAP_FLOAT_OOB_FILL_NONE) == CUDA_SUCCESS;
        }
        {
            const cuuint64_t dims[2] = {DM, (cuuint64_t)HQ * DH}, str[1] = {DM * 2};
            const cuuint32_t box[2] = {16, 256};
            ok &= enc(&m.wo[br], CU_TENSOR_MAP_DATA_TYPE_BFLOAT16, 2, d_in[br * 5 + 4], dims, str, box, es, CU_TENSOR_MAP_INTERLEAVE_NONE,
                      CU_TENSOR_MAP_SWIZZLE_32B, CU_TENSOR_MAP_L2_PROMOTION_L2_128B, CU_TENSOR_MAP_FLOAT_OOB_FILL_NONE) == CUDA_SUCCESS;
        }
    }
    return ok;
}

}

static int g_tau = (int)(1290.0 / 32768.0 * 1048576.0), g_delta = 1000, g_lead = 1800, g_taper = 875, g_ptaper = 9, g_ostep = WO_STEP;

extern "C" void kernel_launch(void* const* d_in, const int* in_sizes, int n_in, void* d_out, int out_size) {
    (void)in_sizes; (void)n_in; (void)out_size;
    static int fast_ok = -1;
    if (fast_ok < 0) {
        int dev = 0, sms = 0, nb = 0, rsv = 0;
        bool ok = cudaGetDevice(&dev) == cudaSuccess &&
                  cudaDeviceGetAttribute(&sms, cudaDevAttrMultiProcessorCount, dev) == cudaSuccess &&
                  cudaDeviceGetAttribute(&rsv, cudaDevAttrReservedSharedMemoryPerBlock, dev) == cudaSuccess && rsv == (int)SMEM_BASE &&
                  cudaFuncSetAttribute(fused_decode_kernel, cudaFuncAttributeMaxDynamicSharedMemorySize, SMEM_BYTES) == cudaSuccess &&
                  cudaOccupancyMaxActiveBlocksPerMultiprocessor(&nb, fused_decode_kernel, NTHREADS, SMEM_BYTES) == cudaSuccess &&
                  sms * nb >= NCTA;
        int khz = 0, bits = 0;
        if (cudaDeviceGetAttribute(&khz, cudaDevAttrMemoryClockRate, dev) == cudaSuccess &&
            cudaDeviceGetAttribute(&bits, cudaDevAttrGlobalMemoryBusWidth, dev) == cudaSuccess && khz > 0 && bits > 0)
            g_tau = (int)(g_tau * (2619000.0 * 5120.0) / ((double)khz * bits) + 0.5);
        fast_ok = ok ? 1 : 0;
        (void)cudaGetLastError();
    }
    Maps maps;
    if (fast_ok == 1 && encode_maps(maps, d_in)) {
        fused_decode_kernel<<<NCTA, NTHREADS, SMEM_BYTES>>>((const __nv_bfloat16*)d_in[0], (const __nv_bfloat16*)d_in[5],
                                                           (__nv_bfloat16*)d_out, g_tau, g_delta, g_lead, g_taper, g_ptaper, g_ostep, maps);
        return;
    }
    Ptrs p;
    for (int br = 0; br < 2; br++) {
        p.x[br] = (const __nv_bfloat16*)d_in[br * 5 + 0]; p.k[br] = (const __nv_bfloat16*)d_in[br * 5 + 1];
        p.v[br] = (const __nv_bfloat16*)d_in[br * 5 + 2]; p.wq[br] = (const __nv_bfloat16*)d_in[br * 5 + 3];
        p.wo[br] = (const __nv_bfloat16*)d_in[br * 5 + 4];
    }
    fb_qproj<<<2 * NB * HQ * DH / 256, 256>>>(p);
    fb_attn<<<2 * NB * HQ, 128>>>(p);
    fb_oproj<<<(NB * 2 * DM + 127) / 128, 128>>>(p, (__nv_bfloat16*)d_out);
}
```
